```python
import torch

def _softmax(x, axis=-1):
    return torch.softmax(x, dim=axis)
def _gelu(x):
    return torch.nn.functional.gelu(x, approximate="tanh")
def _silu(x):
    return torch.nn.functional.silu(x)
def _sigmoid(x):
    return torch.sigmoid(x)
def _layernorm(x, axis=-1, eps=1e-5):
    m = x.mean(dim=axis, keepdim=True)
    v = x.var(dim=axis, keepdim=True, unbiased=False)
    return (x - m) / torch.sqrt(v + eps)
def _scatter_add(tgt, idx, src, axis=0):
    return tgt.clone().index_add_(axis, idx, src)
def _segment_sum(src, seg, n):
    out = torch.zeros((n,) + src.shape[1:], dtype=src.dtype)
    return out.index_add_(0, seg, src)
def _pad(x, pw):
    flat = tuple(v for pair in reversed(pw) for v in pair)
    return torch.nn.functional.pad(x, flat)

kernel_name = 'gated_mix__linear_kernel_hedgehog__mixer_channel_mlp__prompt'

def setup_inputs():

    _w = (lambda a: (lambda t: t.to(torch.bfloat16) if t.is_floating_point() else t)(torch.as_tensor(a)))
    def _A_setup():
        B, S, D, H = 1, 2048, 1024, 32
        Dh = D // H
        return {
            "x": _w((lambda *s: torch.randn(*s, dtype=torch.bfloat16) * 0.05)(B, S, D)),
            "wqkv": _w((lambda *s: torch.randn(*s, dtype=torch.bfloat16) * 0.8)(D, 3 * D)),
            "w_phi": _w((lambda *s: torch.randn(*s, dtype=torch.bfloat16) * 0.8)(H, Dh, Dh) * (Dh ** -0.5)),
            "wo": _w((lambda *s: torch.randn(*s, dtype=torch.bfloat16) * 0.1)(D, D)),
        }
    _A_in = _A_setup()

    def _B_setup():
        B, S, D, F = 1, 2048, 1024, 3584
        return {
            "x": _w((lambda *s: torch.randn(*s, dtype=torch.bfloat16) * 0.05)(B, S, D)),
            "w1": _w((lambda *s: torch.randn(*s, dtype=torch.bfloat16) * 1.6)(D, F) * (D ** -0.5)),
            "b1": _w((lambda *s: torch.randn(*s, dtype=torch.bfloat16) * 0.4)(F)),
            "w2": _w((lambda *s: torch.randn(*s, dtype=torch.bfloat16) * 0.05)(F, D) * (F ** -0.5)),
            "b2": _w((lambda *s: torch.randn(*s, dtype=torch.bfloat16) * 0.05)(D)),
        }
    _B_in = _B_setup()

    return {
        "A_x": _A_in["x"],
        "A_wqkv": _A_in["wqkv"],
        "A_w_phi": _A_in["w_phi"],
        "A_wo": _A_in["wo"],
        "B_x": _B_in["x"],
        "B_w1": _B_in["w1"],
        "B_b1": _B_in["b1"],
        "B_w2": _B_in["w2"],
        "B_b2": _B_in["b2"],
        "gate_w": _w((lambda *s: torch.randn(*s, dtype=torch.bfloat16) * 0.05)(1024) * 16.0),
    }

def reference(A_x, A_wqkv, A_w_phi, A_wo, B_x, B_w1, B_b1, B_w2, B_b2, gate_w):
    def _A_ref(x, wqkv, w_phi, wo):
        B, S, D = x.shape
        H = 32; Dh = D // H
        qkv = (lambda x, *d: x.permute(*d))((x @ wqkv).reshape(B, S, 3, H, Dh), 2, 0, 3, 1, 4)
        q, k, v = qkv[0], qkv[1], qkv[2]
        pq = torch.einsum("bhsd,hdf->bhsf", q, w_phi)
        pk = torch.einsum("bhsd,hdf->bhsf", k, w_phi)
        phi_q = torch.concatenate([_softmax(pq, axis=-1), _softmax(-pq, axis=-1)], axis=-1)
        phi_k = torch.concatenate([_softmax(pk, axis=-1), _softmax(-pk, axis=-1)], axis=-1)
        kv = torch.einsum("bhsf,bhsd->bhfd", phi_k, v)
        z  = torch.einsum("bhsf->bhf", phi_k)
        num = torch.einsum("bhqf,bhfd->bhqd", phi_q, kv)
        den = torch.einsum("bhqf,bhf->bhq", phi_q, z)[..., None] + 1e-6
        o = num / den
        return (lambda x, *d: x.permute(*d))(o, 0, 2, 1, 3).reshape(B, S, D) @ wo

    def _B_ref(x, w1, b1, w2, b2):
        y = _layernorm(x, axis=-1)
        h = _gelu(torch.einsum("bsd,df->bsf", y, w1) + b1)
        return torch.einsum("bsf,fd->bsd", h, w2) + b2

    x = A_x
    g = _sigmoid((x * gate_w).sum(-1, keepdims=True))
    a = _A_ref(x, A_wqkv, A_w_phi, A_wo)
    b = _B_ref(x, B_w1, B_b1, B_w2, B_b2)
    return g * a + (1 - g) * b
```

```cpp
#include <cuda_runtime.h>
#include <cuda_bf16.h>
#include <cuda.h>
#include <stdint.h>

#define TIMING 0
#define NOEPI 0
#define NOEPI3 0
#define NS32 5
#define WAITSTAT 0
#define POL_W L2_NORMAL
#define FIRSTFULL 0
#define QSKIP 0
#define KBSTAMP 0

namespace {

constexpr int S_ = 2048, D_ = 1024, F_ = 3584;
constexpr int NCTA = 128;
constexpr int KVP = 40;

__device__ __align__(1024) __nv_bfloat16 g_y[S_ * D_];
__device__ __align__(1024) __nv_bfloat16 g_h[S_ * F_];
__device__ __align__(1024) __nv_bfloat16 g_o[S_ * D_];
__device__ __align__(1024) float g_kv[32 * 64 * KVP];
__device__ __align__(1024) float g_gate[S_];
__device__ __align__(1024) uint32_t g_cnt[81 * 32];
constexpr int C_ZERO = 0, C_KV = 8, C_Y = 16, C_H1 = 32, C_H2 = 48, C_O = 64, C_DONE = 80;

constexpr uint32_t SM_RING = 0;
constexpr uint32_t SM_STG = 147456;
constexpr uint32_t SM_STGH = SM_STG + 16384;
constexpr uint32_t SM_KVZ = SM_STG + 49152;
constexpr uint32_t SM_X = 212992;
constexpr uint32_t SM_MISC = 229376;
constexpr uint32_t SM_TOTAL = 232448;
constexpr uint32_t SM_BAR = SM_MISC;
constexpr uint32_t SM_B1 = SM_MISC + 256;
constexpr uint32_t SM_GATE = SM_MISC + 2048;
constexpr uint32_t SM_B2 = SM_MISC + 2560;
constexpr uint32_t B_FULL48 = SM_BAR + 0;
constexpr uint32_t B_EMPTY48 = SM_BAR + 32;
constexpr uint32_t B_FULL32 = SM_BAR + 64;
constexpr uint32_t B_EMPTY32 = SM_BAR + 112;
constexpr uint32_t B_DUMP = SM_BAR + 160;
constexpr uint32_t B_SFREE = SM_BAR + 192;
constexpr uint32_t B_GATES = SM_BAR + 200;
constexpr uint32_t B_SLO = SM_BAR + 208;

struct Params {
  CUtensorMap xa, y, h, o, wqkv, w1a, w1b, w2, wo, wphi, out;
  const __nv_bfloat16 *A_x, *b1, *b2, *gate_w;
  __nv_bfloat16 *py, *ph, *po;
};

__device__ __forceinline__ uint32_t smem_u32(const void* p) { return (uint32_t)__cvta_generic_to_shared(p); }
__device__ __forceinline__ void mbar_init(uint32_t bar, uint32_t cnt) {
  asm volatile("mbarrier.init.shared::cta.b64 [%0], %1;" ::"r"(bar), "r"(cnt) : "memory");
}
__device__ __forceinline__ void mbar_expect_tx(uint32_t bar, uint32_t bytes) {
  asm volatile("mbarrier.arrive.expect_tx.shared::cta.b64 _, [%0], %1;" ::"r"(bar), "r"(bytes) : "memory");
}
__device__ __forceinline__ void mbar_arrive(uint32_t bar) {
  asm volatile("mbarrier.arrive.shared::cta.b64 _, [%0];" ::"r"(bar) : "memory");
}
__device__ __forceinline__ void mbar_arrive_cluster(uint32_t bar, uint32_t cta) {
  asm volatile(
      "{\n.reg .b32 ra;\nmapa.shared::cluster.u32 ra, %0, %1;\n"
      "mbarrier.arrive.shared::cluster.b64 _, [ra];\n}" ::"r"(bar), "r"(cta) : "memory");
}
__device__ __forceinline__ void mbar_wait(uint32_t bar, uint32_t parity) {
  asm volatile(
      "{\n.reg .pred p;\n.reg .u32 it;\nmov.u32 it, 0;\n"
      "MW_LOOP:\nmbarrier.try_wait.parity.shared::cta.b64 p, [%0], %1;\n@p bra MW_DONE;\n"
      "add.u32 it, it, 1;\nsetp.lt.u32 p, it, 4194304;\n@p bra MW_LOOP;\ntrap;\nMW_DONE:\n}" ::"r"(bar), "r"(parity) : "memory");
}
__device__ __forceinline__ bool mbar_test(uint32_t bar, uint32_t parity) {
  uint32_t ok;
  asm volatile("{\n.reg .pred p;\nmbarrier.test_wait.parity.shared::cta.b64 p, [%1], %2;\nselp.u32 %0, 1, 0, p;\n}"
               : "=r"(ok) : "r"(bar), "r"(parity) : "memory");
  return ok != 0;
}
__device__ __forceinline__ void wait_flag(const uint32_t* p, uint32_t target) {
  uint32_t it = 0;
  while (true) {
    uint32_t v;
    asm volatile("ld.acquire.gpu.global.u32 %0, [%1];" : "=r"(v) : "l"(p) : "memory");
    if ((int32_t)(v - target) >= 0) break;
    __nanosleep(100);
    if (++it > (1u << 22)) __trap();
  }
}
__device__ __forceinline__ uint32_t load_epoch() {
  uint32_t done;
  asm volatile("ld.relaxed.gpu.global.u32 %0, [%1];" : "=r"(done) : "l"(g_cnt + C_DONE * 32) : "memory");
  return done / NCTA + 1;
}
__device__ __forceinline__ void signal_flag(uint32_t* p) {
  asm volatile("red.release.gpu.global.add.u32 [%0], 1;" ::"l"(p) : "memory");
}
__device__ __forceinline__ void fence_async_all() { asm volatile("fence.proxy.async.global;" ::: "memory"); }
__device__ __forceinline__ void fence_async_smem() { asm volatile("fence.proxy.async.shared::cta;" ::: "memory"); }
constexpr uint64_t L2_NORMAL = 0x1000000000000000ull, L2_FIRST = 0x12F0000000000000ull;
__device__ __forceinline__ void tma_2d(uint32_t dst, const CUtensorMap* m, uint32_t bar, int c0, int c1, uint64_t pol) {
  asm volatile(
      "cp.async.bulk.tensor.2d.shared::cluster.global.mbarrier::complete_tx::bytes.L2::cache_hint [%0], [%1, {%3, %4}], [%2], %5;" ::"r"(dst),
      "l"(m), "r"(bar), "r"(c0), "r"(c1), "l"(pol) : "memory");
}
__device__ __forceinline__ void tma_2d_mc(uint32_t dst, const CUtensorMap* m, uint32_t bar, int c0, int c1, uint64_t pol) {
  asm volatile(
      "cp.async.bulk.tensor.2d.shared::cluster.global.mbarrier::complete_tx::bytes.multicast::cluster.L2::cache_hint [%0], [%1, {%3, "
      "%4}], [%2], %5, %6;" ::"r"(dst),
      "l"(m), "r"(bar), "r"(c0), "r"(c1), "h"((uint16_t)3), "l"(pol) : "memory");
}
__device__ __forceinline__ void tma_3d(uint32_t dst, const CUtensorMap* m, uint32_t bar, int c0, int c1, int c2, uint64_t pol) {
  asm volatile(
      "cp.async.bulk.tensor.3d.shared::cluster.global.mbarrier::complete_tx::bytes.L2::cache_hint [%0], [%1, {%3, %4, %5}], [%2], %6;" ::"r"(dst),
      "l"(m), "r"(bar), "r"(c0), "r"(c1), "r"(c2), "l"(pol) : "memory");
}
__device__ __forceinline__ void tma_store_2d(const CUtensorMap* m, uint32_t src, int c0, int c1) {
  asm volatile("cp.async.bulk.tensor.2d.global.shared::cta.bulk_group [%0, {%2, %3}], [%1];" ::"l"(m), "r"(src), "r"(c0),
               "r"(c1) : "memory");
}
__device__ __forceinline__ void prefetch_tmap(const CUtensorMap* m) {
  asm volatile("prefetch.tensormap [%0];" ::"l"(m) : "memory");
}
__device__ __forceinline__ bool elect_one() {
  uint32_t pred = 0, laneid = 0;
  asm volatile(
      "{\n.reg .b32 rx;\n.reg .pred px;\nelect.sync rx|px, %2;\n@px mov.s32 %1, 1;\nmov.s32 %0, rx;\n}\n"
      : "+r"(laneid), "+r"(pred) : "r"(0xFFFFFFFFu));
  return pred != 0;
}
__device__ __forceinline__ void wg_fence() { asm volatile("wgmma.fence.sync.aligned;" ::: "memory"); }
__device__ __forceinline__ void wg_commit() { asm volatile("wgmma.commit_group.sync.aligned;" ::: "memory"); }
template <int N>
__device__ __forceinline__ void wg_wait() { asm volatile("wgmma.wait_group.sync.aligned %0;" ::"n"(N) : "memory"); }
__device__ __forceinline__ void epi_bar() { asm volatile("bar.sync 1, 128;" ::: "memory"); }
__device__ __forceinline__ uint32_t pack_bf16(float lo, float hi) {
  uint32_t r;
  asm("cvt.rn.bf16x2.f32 %0, %1, %2;" : "=r"(r) : "f"(hi), "f"(lo));
  return r;
}
__device__ __forceinline__ float bf_lo(uint32_t v) { return __uint_as_float(v << 16); }
__device__ __forceinline__ float bf_hi(uint32_t v) { return __uint_as_float(v & 0xffff0000u); }
__device__ __forceinline__ float ex2f(float x) {
  float r;
  asm("ex2.approx.ftz.f32 %0, %1;" : "=f"(r) : "f"(x));
  return r;
}
__device__ __forceinline__ float rcpf(float x) {
  float r;
  asm("rcp.approx.ftz.f32 %0, %1;" : "=f"(r) : "f"(x));
  return r;
}
__device__ __forceinline__ float tanhf_hw(float x) {
  float r;
  asm("tanh.approx.f32 %0, %1;" : "=f"(r) : "f"(x));
  return r;
}
__device__ __forceinline__ void stsm_x4(uint32_t addr, uint32_t a, uint32_t b, uint32_t c, uint32_t d) {
  asm volatile("stmatrix.sync.aligned.m8n8.x4.shared.b16 [%0], {%1, %2, %3, %4};" ::"r"(addr), "r"(a), "r"(b), "r"(c),
               "r"(d) : "memory");
}
__device__ __forceinline__ float lds_f32(uint32_t a) {
  float v;
  asm volatile("ld.shared.f32 %0, [%1];" : "=f"(v) : "r"(a) : "memory");
  return v;
}
__device__ __forceinline__ void sts_f32(uint32_t a, float v) { asm volatile("st.shared.f32 [%0], %1;" ::"r"(a), "f"(v) : "memory"); }
__device__ __forceinline__ uint64_t make_desc(uint32_t addr, uint32_t lbo, uint32_t sbo, uint32_t swz) {
  return (uint64_t)((addr & 0x3FFFF) >> 4) | ((uint64_t)(lbo >> 4) << 16) | ((uint64_t)(sbo >> 4) << 32) |
         ((uint64_t)swz << 62);
}
template <int N>
__device__ __forceinline__ void fence_regs(float (&d)[N]) {
#pragma unroll
  for (int i = 0; i < N; i++) asm volatile("" : "+f"(d[i])::"memory");
}

__device__ __forceinline__ void wgmma_ss_n192(float (&d)[96], uint64_t da, uint64_t db, int scale_d) {
  asm volatile("{\n.reg .pred p;\nsetp.ne.b32 p, %98, 0;\n"
    "wgmma.mma_async.sync.aligned.m64n192k16.f32.bf16.bf16 "
    "{%0, %1, %2, %3, %4, %5, %6, %7, %8, %9, %10, %11, %12, %13, %14, %15, %16, %17, %18, %19, %20, %21, %22, %23, %24, %25, %26, %27, %28, %29, %30, %31, %32, %33, %34, %35, %36, %37, %38, %39, %40, %41, %42, %43, %44, %45, %46, %47, %48, %49, %50, %51, %52, %53, %54, %55, %56, %57, %58, %59, %60, %61, %62, %63, %64, %65, %66, %67, %68, %69, %70, %71, %72, %73, %74, %75, %76, %77, %78, %79, %80, %81, %82, %83, %84, %85, %86, %87, %88, %89, %90, %91, %92, %93, %94, %95}, %96, %97, p, 1, 1, 0, 1;\n}\n"
    : "+f"(d[0]), "+f"(d[1]), "+f"(d[2]), "+f"(d[3]), "+f"(d[4]), "+f"(d[5]), "+f"(d[6]), "+f"(d[7]), "+f"(d[8]), "+f"(d[9]), "+f"(d[10]), "+f"(d[11]), "+f"(d[12]), "+f"(d[13]), "+f"(d[14]), "+f"(d[15]), "+f"(d[16]), "+f"(d[17]), "+f"(d[18]), "+f"(d[19]), "+f"(d[20]), "+f"(d[21]), "+f"(d[22]), "+f"(d[23]), "+f"(d[24]), "+f"(d[25]), "+f"(d[26]), "+f"(d[27]), "+f"(d[28]), "+f"(d[29]), "+f"(d[30]), "+f"(d[31]), "+f"(d[32]), "+f"(d[33]), "+f"(d[34]), "+f"(d[35]), "+f"(d[36]), "+f"(d[37]), "+f"(d[38]), "+f"(d[39]), "+f"(d[40]), "+f"(d[41]), "+f"(d[42]), "+f"(d[43]), "+f"(d[44]), "+f"(d[45]), "+f"(d[46]), "+f"(d[47]), "+f"(d[48]), "+f"(d[49]), "+f"(d[50]), "+f"(d[51]), "+f"(d[52]), "+f"(d[53]), "+f"(d[54]), "+f"(d[55]), "+f"(d[56]), "+f"(d[57]), "+f"(d[58]), "+f"(d[59]), "+f"(d[60]), "+f"(d[61]), "+f"(d[62]), "+f"(d[63]), "+f"(d[64]), "+f"(d[65]), "+f"(d[66]), "+f"(d[67]), "+f"(d[68]), "+f"(d[69]), "+f"(d[70]), "+f"(d[71]), "+f"(d[72]), "+f"(d[73]), "+f"(d[74]), "+f"(d[75]), "+f"(d[76]), "+f"(d[77]), "+f"(d[78]), "+f"(d[79]), "+f"(d[80]), "+f"(d[81]), "+f"(d[82]), "+f"(d[83]), "+f"(d[84]), "+f"(d[85]), "+f"(d[86]), "+f"(d[87]), "+f"(d[88]), "+f"(d[89]), "+f"(d[90]), "+f"(d[91]), "+f"(d[92]), "+f"(d[93]), "+f"(d[94]), "+f"(d[95])
    : "l"(da), "l"(db), "r"(scale_d));
}
__device__ __forceinline__ void wgmma_ss_n128(float (&d)[64], uint64_t da, uint64_t db, int scale_d) {
  asm volatile("{\n.reg .pred p;\nsetp.ne.b32 p, %66, 0;\n"
    "wgmma.mma_async.sync.aligned.m64n128k16.f32.bf16.bf16 "
    "{%0, %1, %2, %3, %4, %5, %6, %7, %8, %9, %10, %11, %12, %13, %14, %15, %16, %17, %18, %19, %20, %21, %22, %23, %24, %25, %26, %27, %28, %29, %30, %31, %32, %33, %34, %35, %36, %37, %38, %39, %40, %41, %42, %43, %44, %45, %46, %47, %48, %49, %50, %51, %52, %53, %54, %55, %56, %57, %58, %59, %60, %61, %62, %63}, %64, %65, p, 1, 1, 0, 1;\n}\n"
    : "+f"(d[0]), "+f"(d[1]), "+f"(d[2]), "+f"(d[3]), "+f"(d[4]), "+f"(d[5]), "+f"(d[6]), "+f"(d[7]), "+f"(d[8]), "+f"(d[9]), "+f"(d[10]), "+f"(d[11]), "+f"(d[12]), "+f"(d[13]), "+f"(d[14]), "+f"(d[15]), "+f"(d[16]), "+f"(d[17]), "+f"(d[18]), "+f"(d[19]), "+f"(d[20]), "+f"(d[21]), "+f"(d[22]), "+f"(d[23]), "+f"(d[24]), "+f"(d[25]), "+f"(d[26]), "+f"(d[27]), "+f"(d[28]), "+f"(d[29]), "+f"(d[30]), "+f"(d[31]), "+f"(d[32]), "+f"(d[33]), "+f"(d[34]), "+f"(d[35]), "+f"(d[36]), "+f"(d[37]), "+f"(d[38]), "+f"(d[39]), "+f"(d[40]), "+f"(d[41]), "+f"(d[42]), "+f"(d[43]), "+f"(d[44]), "+f"(d[45]), "+f"(d[46]), "+f"(d[47]), "+f"(d[48]), "+f"(d[49]), "+f"(d[50]), "+f"(d[51]), "+f"(d[52]), "+f"(d[53]), "+f"(d[54]), "+f"(d[55]), "+f"(d[56]), "+f"(d[57]), "+f"(d[58]), "+f"(d[59]), "+f"(d[60]), "+f"(d[61]), "+f"(d[62]), "+f"(d[63])
    : "l"(da), "l"(db), "r"(scale_d));
}
__device__ __forceinline__ void wgmma_ss_n40_tt(float (&d)[20], uint64_t da, uint64_t db, int scale_d) {
  asm volatile("{\n.reg .pred p;\nsetp.ne.b32 p, %22, 0;\n"
    "wgmma.mma_async.sync.aligned.m64n40k16.f32.bf16.bf16 "
    "{%0, %1, %2, %3, %4, %5, %6, %7, %8, %9, %10, %11, %12, %13, %14, %15, %16, %17, %18, %19}, %20, %21, p, 1, 1, 1, 1;\n}\n"
    : "+f"(d[0]), "+f"(d[1]), "+f"(d[2]), "+f"(d[3]), "+f"(d[4]), "+f"(d[5]), "+f"(d[6]), "+f"(d[7]), "+f"(d[8]), "+f"(d[9]), "+f"(d[10]), "+f"(d[11]), "+f"(d[12]), "+f"(d[13]), "+f"(d[14]), "+f"(d[15]), "+f"(d[16]), "+f"(d[17]), "+f"(d[18]), "+f"(d[19])
    : "l"(da), "l"(db), "r"(scale_d));
}
__device__ __forceinline__ void wgmma_rs_n32(float (&d)[16], uint32_t a0, uint32_t a1, uint32_t a2, uint32_t a3, uint64_t db, int scale_d) {
  asm volatile("{\n.reg .pred p;\nsetp.ne.b32 p, %21, 0;\n"
    "wgmma.mma_async.sync.aligned.m64n32k16.f32.bf16.bf16 "
    "{%0, %1, %2, %3, %4, %5, %6, %7, %8, %9, %10, %11, %12, %13, %14, %15}, {%16, %17, %18, %19}, %20, p, 1, 1, 1;\n}\n"
    : "+f"(d[0]), "+f"(d[1]), "+f"(d[2]), "+f"(d[3]), "+f"(d[4]), "+f"(d[5]), "+f"(d[6]), "+f"(d[7]), "+f"(d[8]), "+f"(d[9]), "+f"(d[10]), "+f"(d[11]), "+f"(d[12]), "+f"(d[13]), "+f"(d[14]), "+f"(d[15])
    : "r"(a0), "r"(a1), "r"(a2), "r"(a3), "l"(db), "r"(scale_d));
}
__device__ __forceinline__ void wgmma_ss_n32_nt(float (&d)[16], uint64_t da, uint64_t db, int scale_d) {
  asm volatile("{\n.reg .pred p;\nsetp.ne.b32 p, %18, 0;\n"
    "wgmma.mma_async.sync.aligned.m64n32k16.f32.bf16.bf16 "
    "{%0, %1, %2, %3, %4, %5, %6, %7, %8, %9, %10, %11, %12, %13, %14, %15}, %16, %17, p, 1, 1, 0, 1;\n}\n"
    : "+f"(d[0]), "+f"(d[1]), "+f"(d[2]), "+f"(d[3]), "+f"(d[4]), "+f"(d[5]), "+f"(d[6]), "+f"(d[7]), "+f"(d[8]), "+f"(d[9]), "+f"(d[10]), "+f"(d[11]), "+f"(d[12]), "+f"(d[13]), "+f"(d[14]), "+f"(d[15])
    : "l"(da), "l"(db), "r"(scale_d));
}

template <int N>
struct MMA;
template <>
struct MMA<256> {
  static __device__ __forceinline__ void run(float (&d)[128], uint64_t a, uint64_t b, int s) {
    wgmma_ss_n128(*reinterpret_cast<float(*)[64]>(&d[0]), a, b, s);
    wgmma_ss_n128(*reinterpret_cast<float(*)[64]>(&d[64]), a, b + 1024, s);
  }
};
template <>
struct MMA<192> {
  static __device__ __forceinline__ void run(float (&d)[96], uint64_t a, uint64_t b, int s) { wgmma_ss_n192(d, a, b, s); }
};
template <>
struct MMA<128> {
  static __device__ __forceinline__ void run(float (&d)[64], uint64_t a, uint64_t b, int s) { wgmma_ss_n128(d, a, b, s); }
};

#define TSTAMP(idx)
#define TSTAMP_IF(c, idx)

template <int NS, uint32_t PITCH, bool ROT>
struct Ring {
  int slot = 0;
  uint32_t ph = 0;
  uint32_t fullb, emptyb;
  __device__ __forceinline__ uint32_t off() const { return ROT ? (slot == 0 ? 2 * PITCH : (slot - 1) * PITCH) : slot * PITCH; }
  __device__ __forceinline__ void wait_full() const { mbar_wait(fullb + 8 * slot, ph); }
  __device__ __forceinline__ bool test_full() const { return mbar_test(fullb + 8 * slot, ph); }
  __device__ __forceinline__ void advance() { if (++slot == NS) { slot = 0; ph ^= 1; } }
  __device__ __forceinline__ void release(int s, int t) const {
    if ((t & 95) == 0) mbar_arrive_cluster(emptyb + 8 * s, t >> 5);
  }
};
template <int N, class R>
__device__ __forceinline__ void mainloop(float (&acc)[N / 2], int nkb, R& ring, uint32_t sb, int w, int t, int ebase) {
  const uint64_t dA0 = make_desc(sb + SM_RING + w * 8192, 16, 1024, 1);
  const uint64_t dB0 = make_desc(sb + SM_RING + 16384, 8192, 1024, 1);
  int prev = 0;
  for (int kb = 0; kb < nkb; kb++) {
    bool pending = kb > 0;
    if (!ring.test_full()) {
      if (pending) {
        wg_wait<0>();
        ring.release(prev, t);
        pending = false;
      }
      ring.wait_full();
    }
    if (KBSTAMP) TSTAMP_IF(t == 0 && w == 0, 64 + ebase + kb);
    const uint64_t o = (uint64_t)(ring.off() >> 4);
    wg_fence();
    MMA<N>::run(acc, dA0 + o, dB0 + o, kb ? 1 : 0);
    wg_commit();
    if (pending) {
      wg_wait<1>();
      ring.release(prev, t);
    }
#pragma unroll
    for (int k = 1; k < 4; k++) MMA<N>::run(acc, dA0 + o + k * 2, dB0 + o + k * 128, 1);
    wg_commit();
    prev = ring.slot;
    ring.advance();
  }
  wg_wait<0>();
  ring.release(prev, t);
  fence_regs(acc);
}

__device__ __forceinline__ uint32_t bmax2(uint32_t a, uint32_t b) { uint32_t r; asm("max.bf16x2 %0, %1, %2;" : "=r"(r) : "r"(a), "r"(b)); return r; }
__device__ __forceinline__ uint32_t bmin2(uint32_t a, uint32_t b) { uint32_t r; asm("min.bf16x2 %0, %1, %2;" : "=r"(r) : "r"(a), "r"(b)); return r; }
__device__ __forceinline__ float4 lds128f(uint32_t a) {
  float4 v;
  asm volatile("ld.shared.v4.f32 {%0, %1, %2, %3}, [%4];" : "=f"(v.x), "=f"(v.y), "=f"(v.z), "=f"(v.w) : "r"(a));
  return v;
}
template <bool DEN>
__device__ __forceinline__ float hedgehog_row(const uint32_t (&w)[16], uint32_t (&out)[32], uint32_t zaddr) {
  constexpr float L2E = 1.4426950408889634f;
  uint32_t mx2[8], mn2[8];
#pragma unroll
  for (int i = 0; i < 8; i++) { mx2[i] = bmax2(w[2 * i], w[2 * i + 1]); mn2[i] = bmin2(w[2 * i], w[2 * i + 1]); }
#pragma unroll
  for (int st = 4; st > 0; st >>= 1)
#pragma unroll
    for (int i = 0; i < st; i++) { mx2[i] = bmax2(mx2[i], mx2[i + st]); mn2[i] = bmin2(mn2[i], mn2[i + st]); }
  const float a = -fmaxf(bf_lo(mx2[0]), bf_hi(mx2[0])) * L2E;
  const float b = fminf(bf_lo(mn2[0]), bf_hi(mn2[0])) * L2E;
  float den = 0.f;
#pragma unroll
  for (int sgn = 0; sgn < 2; sgn++) {
    const float mul = sgn ? -L2E : L2E, off = sgn ? b : a;
    float e[32];
#pragma unroll
    for (int i = 0; i < 16; i++) {
      e[2 * i] = ex2f(fmaf(bf_lo(w[i]), mul, off));
      e[2 * i + 1] = ex2f(fmaf(bf_hi(w[i]), mul, off));
    }
    float s0 = 0.f, s1 = 0.f, s2 = 0.f, s3 = 0.f;
#pragma unroll
    for (int i = 0; i < 8; i++) { s0 += e[4 * i]; s1 += e[4 * i + 1]; s2 += e[4 * i + 2]; s3 += e[4 * i + 3]; }
    const float r = rcpf((s0 + s1) + (s2 + s3));
    if (DEN) {
      float d0 = 0.f, d1 = 0.f, d2 = 0.f, d3 = 0.f;
#pragma unroll
      for (int i = 0; i < 8; i++) {
        const float4 z = lds128f(zaddr + sgn * 128 + i * 16);
        d0 = fmaf(e[4 * i], z.x, d0); d1 = fmaf(e[4 * i + 1], z.y, d1);
        d2 = fmaf(e[4 * i + 2], z.z, d2); d3 = fmaf(e[4 * i + 3], z.w, d3);
      }
      den = fmaf((d0 + d1) + (d2 + d3), r, den);
    }
#pragma unroll
    for (int i = 0; i < 16; i++) out[16 * sgn + i] = pack_bf16(e[2 * i] * r, e[2 * i + 1] * r);
  }
  return den;
}
__device__ __forceinline__ uint4 lds128(uint32_t a) {
  uint4 v;
  asm volatile("ld.shared.v4.u32 {%0, %1, %2, %3}, [%4];" : "=r"(v.x), "=r"(v.y), "=r"(v.z), "=r"(v.w) : "r"(a) : "memory");
  return v;
}
__device__ __forceinline__ void sts128(uint32_t a, uint32_t x, uint32_t y, uint32_t z, uint32_t w) {
  asm volatile("st.shared.v4.u32 [%0], {%1, %2, %3, %4};" ::"r"(a), "r"(x), "r"(y), "r"(z), "r"(w) : "memory");
}

__device__ __forceinline__ float gelu_s(float v, float s) {
  constexpr float C0 = 0.7978845608028654f, C1 = 0.7978845608028654f * 0.044715f;
  const float u = v * fmaf(v * v, C1, C0);
  const float hv = v * s;
  return fmaf(hv, tanhf_hw(u), hv);
}
__device__ __forceinline__ uint4 gelu8(uint4 x, const float (&b)[8], float s) {
  uint4 r;
  r.x = pack_bf16(gelu_s(bf_lo(x.x) + b[0], s), gelu_s(bf_hi(x.x) + b[1], s));
  r.y = pack_bf16(gelu_s(bf_lo(x.y) + b[2], s), gelu_s(bf_hi(x.y) + b[3], s));
  r.z = pack_bf16(gelu_s(bf_lo(x.z) + b[4], s), gelu_s(bf_hi(x.z) + b[5], s));
  r.w = pack_bf16(gelu_s(bf_lo(x.w) + b[6], s), gelu_s(bf_hi(x.w) + b[7], s));
  return r;
}
__device__ __forceinline__ float warp_sum(float v) {
#pragma unroll
  for (int o = 16; o > 0; o >>= 1) v += __shfl_xor_sync(0xffffffffu, v, o);
  return v;
}
__global__ void __cluster_dims__(2, 1, 1) __launch_bounds__(512, 1) fused_kernel(const __grid_constant__ Params P) {
  extern __shared__ __align__(1024) uint8_t smem_raw[];
  const uint32_t sb = smem_u32(smem_raw);
  const int tid = threadIdx.x;
  const int wg = __shfl_sync(0xffffffffu, tid >> 7, 0);
  const int t = tid & 127;
  const int cta = blockIdx.x;
  const int rank = cta & 1;
  const int m = cta >> 3;
  const int nn = ((cta >> 1) & 3) * 2 + rank;

  const int row0 = m * 128;
  if (tid < 32) {
    if (elect_one()) {
      prefetch_tmap(&P.xa);
      prefetch_tmap(&P.wqkv);
      if (sb & 1023) __trap();
#pragma unroll
      for (int s = 0; s < 3; s++) mbar_init(sb + B_FULL48 + 8 * s, 1);
      asm volatile("fence.mbarrier_init.release.cluster;" ::: "memory");
      fence_async_smem();
      TSTAMP(0);
#pragma unroll
      for (int i = 0; i < 3; i++) {
        const uint32_t sa = sb + SM_RING + (i == 0 ? 2 * 49152 : (i - 1) * 49152), fb = sb + B_FULL48 + 8 * i;
        mbar_expect_tx(fb, 49152);
        tma_2d(sa, &P.xa, fb, i * 64, row0, L2_NORMAL);
        tma_3d(sa + 16384, &P.wqkv, fb, 0, i * 64, 16 + 2 * nn, POL_W);
        tma_2d(sa + 8192, &P.xa, fb, i * 64, row0 + 64, L2_NORMAL);
        tma_3d(sa + 32768, &P.wqkv, fb, 0, i * 64, 32 + 2 * nn, POL_W);
      }
      TSTAMP(44);
    }
    __syncwarp();
  } else if (tid == 32) {
    for (int s = 0; s < 3; s++) mbar_init(sb + B_EMPTY48 + 8 * s, 4);
    for (int s = 0; s < NS32; s++) { mbar_init(sb + B_FULL32 + 8 * s, 1); mbar_init(sb + B_EMPTY32 + 8 * s, 4); }
    for (int s = 0; s < 4; s++) mbar_init(sb + B_DUMP + 8 * s, 256);
    mbar_init(sb + B_SFREE, 128);
    mbar_init(sb + B_GATES, 128);
    mbar_init(sb + B_SLO, 128);
    asm volatile("fence.mbarrier_init.release.cluster;" ::: "memory");
  }
  __syncthreads();
  asm volatile("barrier.cluster.arrive.relaxed.aligned;" ::: "memory");

  if (wg == 0) {
    asm volatile("setmaxnreg.dec.sync.aligned.u32 40;");
    const int rowh = row0 + rank * 64;
    asm volatile("barrier.cluster.wait.acquire.aligned;" ::: "memory");
    if (tid < 32 && elect_one()) {
      const uint32_t ep = load_epoch();
      prefetch_tmap(&P.wphi); prefetch_tmap(&P.y); prefetch_tmap(&P.w1a); prefetch_tmap(&P.w1b); prefetch_tmap(&P.h);
      prefetch_tmap(&P.w2); prefetch_tmap(&P.o); prefetch_tmap(&P.wo);
      {
        uint32_t eb = sb + B_EMPTY48, sa = sb + SM_RING + 2 * 49152;
        int s = 0;
        uint32_t ph = 0;
        auto next48 = [&]() {
          if (++s == 3) { s = 0; ph ^= 1; eb = sb + B_EMPTY48; sa = sb + SM_RING + 2 * 49152; }
          else { eb += 8; sa = sb + SM_RING + (s - 1) * 49152; }
        };
        constexpr uint32_t F2E = B_FULL48 - B_EMPTY48;
#pragma unroll 1
        for (int k = 3 * 64; k < 1024; k += 64) {
          mbar_wait(eb, ph);
          mbar_expect_tx(eb + F2E, 49152);
          tma_2d_mc(sa + rank * 8192, &P.xa, eb + F2E, k, rowh, L2_NORMAL);
          tma_3d(sa + 16384, &P.wqkv, eb + F2E, 0, k, 16 + 2 * nn, POL_W);
          tma_3d(sa + 32768, &P.wqkv, eb + F2E, 0, k, 32 + 2 * nn, POL_W);
          next48();
        }
        mbar_wait(eb, ph);
        mbar_expect_tx(eb + F2E, 8192);
        tma_2d(sa, &P.wphi, eb + F2E, 0, nn * 128, L2_NORMAL);
        next48();
        wait_flag(g_cnt + (C_Y + m) * 32, ep * 8);
        fence_async_all();
        TSTAMP(40);
#pragma unroll 1
        for (int k = 0; k < 1024; k += 64) {
          mbar_wait(eb, ph);
          mbar_expect_tx(eb + F2E, 49152);
          tma_2d_mc(sa + rank * 8192, &P.y, eb + F2E, k, rowh, L2_NORMAL);
          tma_3d(sa + 16384, &P.w1a, eb + F2E, 0, k, 7 * nn, POL_W);
          next48();
        }
#pragma unroll 1
        for (int k = 0; k < 1024; k += 64) {
          mbar_wait(eb, ph);
          mbar_expect_tx(eb + F2E, 40960);
          tma_2d_mc(sa + rank * 8192, &P.y, eb + F2E, k, rowh, POL_W);
          tma_3d(sa + 16384, &P.w1b, eb + F2E, 0, k, 7 * nn + 4, POL_W);
          next48();
        }
      }
      uint32_t eb = sb + B_EMPTY32, sa = sb + SM_RING;
      int s = 0;
      uint32_t ph = 1;
      auto next32 = [&]() {
        if (++s == NS32) { s = 0; ph ^= 1; eb = sb + B_EMPTY32; sa = sb + SM_RING; }
        else { eb += 8; sa += 32768; }
      };
      constexpr uint32_t F2E = B_FULL32 - B_EMPTY32;
#pragma unroll 1
      for (int j = 0; j < 16; j++) {
        if (j >= NS32) mbar_wait(eb, ph);
        else if (j == 0) mbar_wait(sb + B_EMPTY48 + 8 * 1, 1);
        else if (j == 1) mbar_wait(sb + B_EMPTY48 + 8 * 2, 1);
        else if (j == 3) mbar_wait(sb + B_EMPTY48 + 8 * 0, 0);
        else if (j == 4) mbar_wait(sb + B_SLO, 0);
        else if (j == 5) mbar_wait(sb + B_DUMP + 16, 0);
        mbar_expect_tx(eb + F2E, 32768);
        tma_2d_mc(sa + rank * 8192, &P.xa, eb + F2E, j * 64, rowh, POL_W);
        tma_3d(sa + 16384, &P.wqkv, eb + F2E, 0, j * 64, 2 * nn, POL_W);
        next32();
      }
      mbar_wait(eb, ph);
      mbar_expect_tx(eb + F2E, 8192);
      tma_2d(sa, &P.wphi, eb + F2E, 0, nn * 128, L2_NORMAL);
      next32();
#pragma unroll 1
      for (int part = 0; part < 2; part++) {
        wait_flag(g_cnt + ((part ? C_H2 : C_H1) + m) * 32, ep * 8);
        fence_async_all();
        TSTAMP(41 + part);
        const int nk = part ? 3 : 4;
#pragma unroll 1
        for (int col0 = part * 256; col0 < F_; col0 += 448) {
#pragma unroll 1
          for (int col = col0; col < col0 + nk * 64; col += 64) {
            mbar_wait(eb, ph);
            mbar_expect_tx(eb + F2E, 32768);
            tma_2d_mc(sa + rank * 8192, &P.h, eb + F2E, col, rowh, POL_W);
            tma_3d(sa + 16384, &P.w2, eb + F2E, 0, col, 2 * nn, POL_W);
            next32();
          }
        }
      }
      wait_flag(g_cnt + (C_O + m) * 32, ep * 8);
      fence_async_all();
      TSTAMP(43);
#pragma unroll 1
      for (int col = 0; col < D_; col += 64) {
        mbar_wait(eb, ph);
        mbar_expect_tx(eb + F2E, 32768);
        tma_2d_mc(sa + rank * 8192, &P.o, eb + F2E, col, rowh, POL_W);
        tma_3d(sa + 16384, &P.wo, eb + F2E, 0, col, 2 * nn, POL_W);
        next32();
      }
#pragma unroll 1
      for (int j = 0; j < NS32; j++) {
        mbar_wait(eb, ph);
        next32();
      }
    }
  } else if (wg <= 2) {
    TSTAMP_IF(tid == 128, 47);
    asm volatile("setmaxnreg.inc.sync.aligned.u32 168;");
    TSTAMP_IF(tid == 128, 48);
    asm volatile("barrier.cluster.wait.acquire.aligned;" ::: "memory");
    TSTAMP_IF(tid == 128, 49);
    const int w = wg - 1;
    const int warp = t >> 5, lane = t & 31, q = lane & 3;
    const int rloc = w * 64 + warp * 16 + (lane >> 2);
    const int srow = w * 64 + warp * 16 + ((lane >> 3) & 1) * 8 + (lane & 7);
    const uint32_t st_row = srow * 128, st_x = srow & 7, st_hi = lane >> 4;
    {
      Ring<3, 49152, true> ring;
      ring.fullb = sb + B_FULL48;
      ring.emptyb = sb + B_EMPTY48;
      {
        float acc[128];
        mainloop<256>(acc, 16, ring, sb, w, t, 0);
        TSTAMP_IF(t == 0, 1 + w);
        {
          uint32_t kp[32], vp[32];
#pragma unroll
          for (int i = 0; i < 32; i++) {
            vp[i] = pack_bf16(acc[64 + 2 * i], acc[64 + 2 * i + 1]);
            asm volatile("" : "+r"(vp[i]));
          }
#pragma unroll
          for (int i = 0; i < 32; i++) kp[i] = pack_bf16(acc[2 * i], acc[2 * i + 1]);
          ring.wait_full();
          const uint64_t dW = make_desc(sb + SM_RING + ring.off(), 16, 512, 2);
          float p[4][16];
          wg_fence();
#pragma unroll
          for (int h = 0; h < 4; h++) {
            wgmma_rs_n32(p[h], kp[8 * h], kp[8 * h + 1], kp[8 * h + 2], kp[8 * h + 3], dW + h * 128, 0);
            wgmma_rs_n32(p[h], kp[8 * h + 4], kp[8 * h + 5], kp[8 * h + 6], kp[8 * h + 7], dW + h * 128 + 64, 1);
          }
          wg_commit();
#pragma unroll
          for (int h = 0; h < 4; h++) {
            const uint32_t tb = sb + SM_STG + h * 16384 + st_row;
            stsm_x4(tb + (((0 + st_hi) ^ st_x) << 4), vp[8 * h], vp[8 * h + 1], vp[8 * h + 2], vp[8 * h + 3]);
            stsm_x4(tb + (((2 + st_hi) ^ st_x) << 4), vp[8 * h + 4], vp[8 * h + 5], vp[8 * h + 6], vp[8 * h + 7]);
          }
          wg_wait<0>();
          ring.release(ring.slot, t);
          ring.advance();
#pragma unroll
          for (int h = 0; h < 4; h++) {
            fence_regs(p[h]);
            const uint32_t tb = sb + SM_STG + h * 16384 + st_row;
            stsm_x4(tb + (((4 + st_hi) ^ st_x) << 4), pack_bf16(p[h][0], p[h][1]), pack_bf16(p[h][2], p[h][3]),
                    pack_bf16(p[h][4], p[h][5]), pack_bf16(p[h][6], p[h][7]));
            stsm_x4(tb + (((6 + st_hi) ^ st_x) << 4), pack_bf16(p[h][8], p[h][9]), pack_bf16(p[h][10], p[h][11]),
                    pack_bf16(p[h][12], p[h][13]), pack_bf16(p[h][14], p[h][15]));
          }
          fence_async_smem();
          mbar_arrive(sb + B_DUMP + 0);
        }
        TSTAMP_IF(t == 0, 3 + w);
      }
      {
        float acc[128];
        mainloop<256>(acc, 16, ring, sb, w, t, 17);
        TSTAMP_IF(t == 0, 5 + w);
        mbar_wait(sb + B_SFREE, 0);
#pragma unroll
        for (int i = 0; i < 16; i++)
          stsm_x4(sb + SM_STG + (i >> 2) * 16384 + st_row + (((2 * (i & 3) + st_hi) ^ st_x) << 4),
                  pack_bf16(acc[8 * i], acc[8 * i + 1]), pack_bf16(acc[8 * i + 2], acc[8 * i + 3]),
                  pack_bf16(acc[8 * i + 4], acc[8 * i + 5]), pack_bf16(acc[8 * i + 6], acc[8 * i + 7]));
        mbar_arrive(sb + B_DUMP + 8);
        TSTAMP_IF(t == 0, 7 + w);
      }
      {
        float acc[96];
        mainloop<192>(acc, 16, ring, sb, w, t, 33);
        TSTAMP_IF(t == 0, 9 + w);
        mbar_wait(sb + B_SFREE, 1);
#pragma unroll
        for (int i = 0; i < 12; i++)
          stsm_x4(sb + SM_STGH + (i >> 2) * 16384 + st_row + (((2 * (i & 3) + st_hi) ^ st_x) << 4),
                  pack_bf16(acc[8 * i], acc[8 * i + 1]), pack_bf16(acc[8 * i + 2], acc[8 * i + 3]),
                  pack_bf16(acc[8 * i + 4], acc[8 * i + 5]), pack_bf16(acc[8 * i + 6], acc[8 * i + 7]));
        mbar_arrive(sb + B_DUMP + 16);
        TSTAMP_IF(t == 0, 11 + w);
      }
    }
    {
      Ring<NS32, 32768, false> ring;
      ring.fullb = sb + B_FULL32;
      ring.emptyb = sb + B_EMPTY32;
      {
        float acc[64];
        mainloop<128>(acc, 16, ring, sb, w, t, 49);
        TSTAMP_IF(t == 0, 13 + w);
        uint32_t qp[32];
#pragma unroll
        for (int i = 0; i < 32; i++) qp[i] = pack_bf16(acc[2 * i], acc[2 * i + 1]);
        ring.wait_full();
        const uint64_t dW = make_desc(sb + SM_RING + ring.off(), 16, 512, 2);
        float p[4][16];
        wg_fence();
#pragma unroll
        for (int h = 0; h < 4; h++) {
          wgmma_rs_n32(p[h], qp[8 * h], qp[8 * h + 1], qp[8 * h + 2], qp[8 * h + 3], dW + h * 128, 0);
          wgmma_rs_n32(p[h], qp[8 * h + 4], qp[8 * h + 5], qp[8 * h + 6], qp[8 * h + 7], dW + h * 128 + 64, 1);
        }
        wg_commit();
        mbar_wait(sb + B_SFREE, 0);
        wg_wait<0>();
        ring.release(ring.slot, t);
        ring.advance();
#pragma unroll
        for (int h = 0; h < 4; h++) {
          fence_regs(p[h]);
          const uint32_t tb = sb + SM_STGH + (h >> 1) * 16384 + st_row;
          stsm_x4(tb + ((((h & 1) * 4 + 0 + st_hi) ^ st_x) << 4), pack_bf16(p[h][0], p[h][1]), pack_bf16(p[h][2], p[h][3]),
                  pack_bf16(p[h][4], p[h][5]), pack_bf16(p[h][6], p[h][7]));
          stsm_x4(tb + ((((h & 1) * 4 + 2 + st_hi) ^ st_x) << 4), pack_bf16(p[h][8], p[h][9]), pack_bf16(p[h][10], p[h][11]),
                  pack_bf16(p[h][12], p[h][13]), pack_bf16(p[h][14], p[h][15]));
        }
        mbar_arrive(sb + B_DUMP + 24);
      }
      TSTAMP_IF(t == 0, 15 + w);
      float acc[64];
      mainloop<128>(acc, 72, ring, sb, w, t, 66);
      TSTAMP_IF(t == 0, 17 + w);
      mbar_wait(sb + B_GATES, 0);
      const float s0 = 1.f - lds_f32(sb + SM_GATE + 4 * rloc), s1 = 1.f - lds_f32(sb + SM_GATE + 4 * (rloc + 8));
      const uint32_t stg = sb + SM_RING + w * 8192 + (st_row - w * 8192);
#pragma unroll
      for (int i = 0; i < 8; i++) {
        const float bA0 = lds_f32(sb + SM_B2 + 4 * (16 * i + 2 * q)), bA1 = lds_f32(sb + SM_B2 + 4 * (16 * i + 2 * q + 1));
        const float bB0 = lds_f32(sb + SM_B2 + 4 * (16 * i + 8 + 2 * q)), bB1 = lds_f32(sb + SM_B2 + 4 * (16 * i + 8 + 2 * q + 1));
        const uint32_t r0 = pack_bf16(fmaf(s0, bA0, acc[8 * i]), fmaf(s0, bA1, acc[8 * i + 1]));
        const uint32_t r1 = pack_bf16(fmaf(s1, bA0, acc[8 * i + 2]), fmaf(s1, bA1, acc[8 * i + 3]));
        const uint32_t r2 = pack_bf16(fmaf(s0, bB0, acc[8 * i + 4]), fmaf(s0, bB1, acc[8 * i + 5]));
        const uint32_t r3 = pack_bf16(fmaf(s1, bB0, acc[8 * i + 6]), fmaf(s1, bB1, acc[8 * i + 7]));
        stsm_x4(stg + (i >> 2) * 32768 + (((2 * (i & 3) + st_hi) ^ st_x) << 4), r0, r1, r2, r3);
      }
      fence_async_smem();
      if (w == 0) asm volatile("bar.sync 2, 128;" ::: "memory");
      else asm volatile("bar.sync 3, 128;" ::: "memory");
      if (t == 0) {
        tma_store_2d(&P.out, sb + SM_RING + w * 8192, 128 * nn, m * 128 + w * 64);
        tma_store_2d(&P.out, sb + SM_RING + w * 8192 + 32768, 128 * nn + 64, m * 128 + w * 64);
        asm volatile("cp.async.bulk.commit_group;" ::: "memory");
        asm volatile("cp.async.bulk.wait_group.read 0;" ::: "memory");
        TSTAMP(19 + w);
      }
    }
  } else {
    asm volatile("setmaxnreg.inc.sync.aligned.u32 136;");
    const int warp = t >> 5, lane = t & 31, q = lane & 3;
    TSTAMP_IF(t == 0, 45);
    uint32_t ep = 0;
    if (t == 0) ep = load_epoch();
    {
      const int r0 = m * 128 + nn * 16 + warp * 4;
      uint4 gw[4], xb[4][4];
#pragma unroll
      for (int u = 0; u < 4; u++)
#pragma unroll
        for (int i = 0; i < 4; i++)
          xb[u][i] = __ldg(reinterpret_cast<const uint4*>(P.A_x + (size_t)(r0 + u) * D_) + lane + 32 * i);
#pragma unroll
      for (int i = 0; i < 4; i++) gw[i] = __ldg(reinterpret_cast<const uint4*>(P.gate_w) + lane + 32 * i);
      {
        uint4* z = reinterpret_cast<uint4*>(g_kv + (size_t)nn * 4 * 64 * KVP) + m * 160;
        z[t] = make_uint4(0, 0, 0, 0);
        if (t < 32) z[128 + t] = make_uint4(0, 0, 0, 0);
      }
#pragma unroll
      for (int u = 0; u < 4; u++) {
        float sum = 0.f, dot = 0.f;
#pragma unroll
        for (int i = 0; i < 4; i++) {
          const uint32_t b[4] = {xb[u][i].x, xb[u][i].y, xb[u][i].z, xb[u][i].w};
          const uint32_t g[4] = {gw[i].x, gw[i].y, gw[i].z, gw[i].w};
#pragma unroll
          for (int k = 0; k < 4; k++) {
            sum += bf_lo(b[k]) + bf_hi(b[k]);
            dot = fmaf(bf_lo(b[k]), bf_lo(g[k]), dot);
            dot = fmaf(bf_hi(b[k]), bf_hi(g[k]), dot);
          }
        }
        const float mean = warp_sum(sum) * (1.f / D_);
        dot = warp_sum(dot);
        float var = 0.f;
#pragma unroll
        for (int i = 0; i < 4; i++) {
          const uint32_t b[4] = {xb[u][i].x, xb[u][i].y, xb[u][i].z, xb[u][i].w};
#pragma unroll
          for (int k = 0; k < 4; k++) {
            const float d0 = bf_lo(b[k]) - mean, d1 = bf_hi(b[k]) - mean;
            var = fmaf(d0, d0, var);
            var = fmaf(d1, d1, var);
          }
        }
        var = warp_sum(var) * (1.f / D_);
        const float rstd = rsqrtf(var + 1e-5f);
        uint4* dsty = reinterpret_cast<uint4*>(P.py + (size_t)(r0 + u) * D_) + lane;
#pragma unroll
        for (int i = 0; i < 4; i++) {
          const uint32_t b[4] = {xb[u][i].x, xb[u][i].y, xb[u][i].z, xb[u][i].w};
          uint32_t o[4];
#pragma unroll
          for (int k = 0; k < 4; k++) o[k] = pack_bf16((bf_lo(b[k]) - mean) * rstd, (bf_hi(b[k]) - mean) * rstd);
          dsty[32 * i] = make_uint4(o[0], o[1], o[2], o[3]);
        }
        if (lane == 0) g_gate[r0 + u] = 1.f / (1.f + __expf(-dot));
      }
      TSTAMP_IF(t == 0, 46);
      fence_async_all();
      epi_bar();
      if (t == 0) {
        signal_flag(g_cnt + (C_Y + m) * 32);
        signal_flag(g_cnt + (C_ZERO + nn) * 32);
        TSTAMP(21);
      }
    }
    asm volatile("barrier.cluster.wait.acquire.aligned;" ::: "memory");
    {
      for (int p = t; p < 448; p += 128) sts_f32(sb + SM_B1 + 4 * p, __bfloat162float(P.b1[448 * nn + p]));
      sts_f32(sb + SM_B2 + 4 * t, __bfloat162float(P.b2[128 * nn + t]));
      if (t == 0) {
        wait_flag(g_cnt + (C_Y + m) * 32, ep * 8);
        wait_flag(g_cnt + (C_ZERO + nn) * 32, ep * 16);
      }
      epi_bar();
      sts_f32(sb + SM_GATE + 4 * t, __ldcg(g_gate + m * 128 + t));
      mbar_arrive(sb + B_GATES);
      epi_bar();
    }
    const uint32_t my_row = t * 128, my_x = t & 7;
    {
      mbar_wait(sb + B_DUMP + 0, 0);
      TSTAMP_IF(t == 0, 22);
      const uint64_t dPhi = make_desc(sb + SM_X, 1024, 1024, 1);
      float kv[20];
#pragma unroll
      for (int i = 0; i < 20; i++) kv[i] = 0.f;
      float* dst = g_kv + ((size_t)(nn * 4) * 64 + warp * 16 + (lane >> 2)) * KVP;
#pragma unroll 1
      for (int h = 0; h < (NOEPI ? 0 : 4); h++) {
        const uint32_t tb = sb + SM_STG + h * 16384 + my_row;
        uint32_t pw[16];
#pragma unroll
        for (int c = 0; c < 4; c++) {
          const uint4 v = lds128(tb + (((4 + c) ^ my_x) << 4));
          pw[4 * c] = v.x; pw[4 * c + 1] = v.y; pw[4 * c + 2] = v.z; pw[4 * c + 3] = v.w;
        }
        sts128(tb + ((4 ^ my_x) << 4), 0x00003f80u, 0u, 0u, 0u);
        uint32_t phi[32];
        hedgehog_row<false>(pw, phi, 0);
        TSTAMP_IF(t == 0, 400 + 4 * h);
        if (h > 0) {
          wg_wait<0>();
          fence_regs(kv);
#pragma unroll
          for (int j = 0; j < 4; j++) {
            asm volatile("red.global.add.v2.f32 [%0], {%1, %2};" ::"l"(dst + 8 * j + 2 * q), "f"(kv[4 * j]), "f"(kv[4 * j + 1]) : "memory");
            asm volatile("red.global.add.v2.f32 [%0], {%1, %2};" ::"l"(dst + 8 * KVP + 8 * j + 2 * q), "f"(kv[4 * j + 2]), "f"(kv[4 * j + 3]) : "memory");
          }
          if (q == 0) {
            asm volatile("red.global.add.f32 [%0], %1;" ::"l"(dst + 32), "f"(kv[16]) : "memory");
            asm volatile("red.global.add.f32 [%0], %1;" ::"l"(dst + 8 * KVP + 32), "f"(kv[18]) : "memory");
          }
          dst += 64 * KVP;
        }
        epi_bar();
        TSTAMP_IF(t == 0, 401 + 4 * h);
#pragma unroll
        for (int c = 0; c < 8; c++)
          sts128(sb + SM_X + my_row + ((c ^ my_x) << 4), phi[4 * c], phi[4 * c + 1], phi[4 * c + 2], phi[4 * c + 3]);
        fence_async_smem();
        epi_bar();
        TSTAMP_IF(t == 0, 402 + 4 * h);
        const uint64_t dV = make_desc(sb + SM_STG + h * 16384, 1024, 1024, 1);
        wg_fence();
#pragma unroll
        for (int k = 0; k < 8; k++) wgmma_ss_n40_tt(kv, dPhi + k * 128, dV + k * 128, k);
        wg_commit();
        TSTAMP_IF(t == 0, 403 + 4 * h);
      }
      wg_wait<0>();
      fence_regs(kv);
      mbar_arrive(sb + B_SFREE);
#pragma unroll
      for (int j = 0; j < 4; j++) {
        asm volatile("red.global.add.v2.f32 [%0], {%1, %2};" ::"l"(dst + 8 * j + 2 * q), "f"(kv[4 * j]), "f"(kv[4 * j + 1]) : "memory");
        asm volatile("red.global.add.v2.f32 [%0], {%1, %2};" ::"l"(dst + 8 * KVP + 8 * j + 2 * q), "f"(kv[4 * j + 2]), "f"(kv[4 * j + 3]) : "memory");
      }
      if (q == 0) {
        asm volatile("red.global.add.f32 [%0], %1;" ::"l"(dst + 32), "f"(kv[16]) : "memory");
        asm volatile("red.global.add.f32 [%0], %1;" ::"l"(dst + 8 * KVP + 32), "f"(kv[18]) : "memory");
      }
      epi_bar();
      if (t == 0) { signal_flag(g_cnt + (C_KV + nn) * 32); TSTAMP(23); }
    }
    {
      float b[8];
#pragma unroll
      for (int i = 0; i < 8; i++) b[i] = lds_f32(sb + SM_B1 + 4 * (8 * lane + i));
      __nv_bfloat16* base = P.ph + (size_t)(m * 128 + warp * 32) * F_ + 448 * nn + 8 * lane;
      const uint32_t src = sb + SM_STG + (lane >> 3) * 16384 + warp * 32 * 128;
      mbar_wait(sb + B_DUMP + 8, 0);
      TSTAMP_IF(t == 0, 24);
#pragma unroll 1
      for (int r = 0; r < (NOEPI ? 0 : 32); r += 4) {
        uint4 x[4];
        float s[4];
#pragma unroll
        for (int u = 0; u < 4; u++) {
          x[u] = lds128(src + (r + u) * 128 + (((lane & 7) ^ ((r + u) & 7)) << 4));
          s[u] = 0.5f - 0.5f * lds_f32(sb + SM_GATE + 4 * (warp * 32 + r + u));
        }
#pragma unroll
        for (int u = 0; u < 4; u++) *reinterpret_cast<uint4*>(base + (size_t)(r + u) * F_) = gelu8(x[u], b, s[u]);
      }
      mbar_arrive(sb + B_SFREE);
      mbar_arrive(sb + B_SLO);
      fence_async_all();
      epi_bar();
      if (t == 0) { signal_flag(g_cnt + (C_H1 + m) * 32); TSTAMP(25); }
    }
    {
      float b[3][8];
      int ro[3], co[3];
#pragma unroll
      for (int u = 0; u < 3; u++) {
        const int L = u * 32 + lane;
        ro[u] = L / 24;
        co[u] = L % 24;
#pragma unroll
        for (int i = 0; i < 8; i++) b[u][i] = lds_f32(sb + SM_B1 + 4 * (256 + 8 * co[u] + i));
      }
      __nv_bfloat16* base = P.ph + (size_t)(m * 128 + warp * 32) * F_ + 448 * nn + 256;
      mbar_wait(sb + B_DUMP + 16, 0);
      TSTAMP_IF(t == 0, 26);
#pragma unroll 1
      for (int r = 0; r < (NOEPI ? 0 : 32); r += 4) {
        uint4 x[3];
        float s[3];
#pragma unroll
        for (int u = 0; u < 3; u++) {
          const int row = warp * 32 + r + ro[u];
          x[u] = lds128(sb + SM_STGH + (co[u] >> 3) * 16384 + row * 128 + (((co[u] & 7) ^ (row & 7)) << 4));
          s[u] = 0.5f - 0.5f * lds_f32(sb + SM_GATE + 4 * row);
        }
#pragma unroll
        for (int u = 0; u < 3; u++) *reinterpret_cast<uint4*>(base + (size_t)(r + ro[u]) * F_ + 8 * co[u]) = gelu8(x[u], b[u], s[u]);
      }
      mbar_arrive(sb + B_SFREE);
      fence_async_all();
      epi_bar();
      if (t == 0) { signal_flag(g_cnt + (C_H2 + m) * 32); TSTAMP(27); }
    }
    {
      constexpr uint32_t SM_Z = SM_B1, SM_DEN = SM_B1 + 1024;
      if (t == 0) wait_flag(g_cnt + (C_KV + nn) * 32, ep * 16);
      epi_bar();
      {
        const float* ksrc = g_kv + (size_t)(nn * 4) * 64 * KVP;
        const float z0 = __ldcg(ksrc + t * KVP + 32), z1 = __ldcg(ksrc + (128 + t) * KVP + 32);
#pragma unroll
        for (int hp = 0; hp < 2; hp++) {
          float4 kvv[8];
#pragma unroll
          for (int u = 0; u < 8; u++) {
            const int idx = (hp * 8 + u) * 128 + t;
            kvv[u] = __ldcg(reinterpret_cast<const float4*>(ksrc + (idx >> 3) * KVP + 4 * (idx & 7)));
          }
#pragma unroll
          for (int u = 0; u < 8; u++) {
            const int idx = (hp * 8 + u) * 128 + t, f = idx >> 3, c4 = idx & 7;
            asm volatile("st.shared.v2.u32 [%0], {%1, %2};" ::"r"(sb + SM_KVZ + f * 64 + (((c4 >> 1) ^ ((f >> 1) & 3)) << 4) + (c4 & 1) * 8),
                         "r"(pack_bf16(kvv[u].x, kvv[u].y)), "r"(pack_bf16(kvv[u].z, kvv[u].w)) : "memory");
          }
        }
        sts_f32(sb + SM_Z + 4 * t, bf_lo(pack_bf16(z0, z0)));
        sts_f32(sb + SM_Z + 4 * (128 + t), bf_lo(pack_bf16(z1, z1)));
      }
      mbar_wait(sb + B_DUMP + 24, 0);
      epi_bar();
      TSTAMP_IF(t == 0, 28);
#pragma unroll 1
      for (int h = 0; h < ((NOEPI || NOEPI3) ? 0 : 4); h++) {
        const uint32_t tb = sb + SM_STGH + (h >> 1) * 16384 + my_row;
        uint32_t pw[16];
#pragma unroll
        for (int c = 0; c < 4; c++) {
          const uint4 v = lds128(tb + ((((h & 1) * 4 + c) ^ my_x) << 4));
          pw[4 * c] = v.x; pw[4 * c + 1] = v.y; pw[4 * c + 2] = v.z; pw[4 * c + 3] = v.w;
        }
        TSTAMP_IF(t == 0 && h == 1, 420);
        uint32_t phi[32];
        const float den = hedgehog_row<true>(pw, phi, sb + SM_Z + h * 256);
        TSTAMP_IF(t == 0 && h == 1, 421);
        epi_bar();
        TSTAMP_IF(t == 0 && h == 1, 422);
#pragma unroll
        for (int c = 0; c < 8; c++)
          sts128(sb + SM_X + my_row + ((c ^ my_x) << 4), phi[4 * c], phi[4 * c + 1], phi[4 * c + 2], phi[4 * c + 3]);
        sts_f32(sb + SM_DEN + 4 * t, lds_f32(sb + SM_GATE + 4 * t) * rcpf(den + 1e-6f));
        TSTAMP_IF(t == 0 && h == 1, 423);
        fence_async_smem();
        epi_bar();
        TSTAMP_IF(t == 0 && h == 1, 424);
        const uint64_t dK = make_desc(sb + SM_KVZ + h * 4096, 16, 512, 2);
        const uint64_t dQ = make_desc(sb + SM_X, 16, 1024, 1);
        float nd[2][16];
        wg_fence();
#pragma unroll
        for (int hf = 0; hf < 2; hf++)
#pragma unroll
          for (int k = 0; k < ((QSKIP & 2) ? 1 : 4); k++) wgmma_ss_n32_nt(nd[hf], dQ + hf * 512 + k * 2, dK + k * 64, k);
        wg_commit();
        TSTAMP_IF(t == 0 && h == 1, 425);
        wg_wait<0>();
        TSTAMP_IF(t == 0 && h == 1, 426);
#pragma unroll
        for (int hf = 0; hf < 2; hf++) {
          fence_regs(nd[hf]);
          const int rl = hf * 64 + warp * 16 + (lane >> 2);
          const float f0 = lds_f32(sb + SM_DEN + 4 * rl), f1 = lds_f32(sb + SM_DEN + 4 * (rl + 8));
          const int srow = hf * 64 + warp * 16 + ((lane >> 3) & 1) * 8 + (lane & 7);
          const uint32_t ob = sb + SM_STGH + (h >> 1) * 16384 + srow * 128;
#pragma unroll
          for (int c = 0; c < 2; c++)
            stsm_x4(ob + ((((h & 1) * 4 + 2 * c + (lane >> 4)) ^ (srow & 7)) << 4),
                    pack_bf16(nd[hf][8 * c] * f0, nd[hf][8 * c + 1] * f0), pack_bf16(nd[hf][8 * c + 2] * f1, nd[hf][8 * c + 3] * f1),
                    pack_bf16(nd[hf][8 * c + 4] * f0, nd[hf][8 * c + 5] * f0), pack_bf16(nd[hf][8 * c + 6] * f1, nd[hf][8 * c + 7] * f1));
        }
        TSTAMP_IF(t == 0 && h == 1, 427);
        TSTAMP_IF(t == 0 && h == 0, 419);
      }
      fence_async_smem();
      epi_bar();
      if (t == 0) {
        if (!(QSKIP & 4)) {
#pragma unroll
          for (int i = 0; i < 4; i++)
            tma_store_2d(&P.o, sb + SM_STGH + (i >> 1) * 16384 + (i & 1) * 8192, 128 * nn + (i >> 1) * 64, m * 128 + (i & 1) * 64);
          asm volatile("cp.async.bulk.commit_group;" ::: "memory");
          asm volatile("cp.async.bulk.wait_group 0;" ::: "memory");
        }
        signal_flag(g_cnt + (C_O + m) * 32);
        TSTAMP(29);
        asm volatile("red.relaxed.gpu.global.add.u32 [%0], 1;" ::"l"(g_cnt + C_DONE * 32) : "memory");
      }
    }
  }
}

typedef CUresult (*EncFn)(CUtensorMap*, CUtensorMapDataType, cuuint32_t, void*, const cuuint64_t*, const cuuint64_t*,
                          const cuuint32_t*, const cuuint32_t*, CUtensorMapInterleave, CUtensorMapSwizzle,
                          CUtensorMapL2promotion, CUtensorMapFloatOOBfill);

void encode(EncFn enc, CUtensorMap* m, int rank, const void* p, const cuuint64_t* dims, const cuuint64_t* strides,
            const cuuint32_t* box, CUtensorMapSwizzle swz) {
  cuuint32_t e[5] = {1, 1, 1, 1, 1};
  enc(m, CU_TENSOR_MAP_DATA_TYPE_BFLOAT16, rank, const_cast<void*>(p), dims, strides, box, e, CU_TENSOR_MAP_INTERLEAVE_NONE, swz,
      CU_TENSOR_MAP_L2_PROMOTION_L2_256B, CU_TENSOR_MAP_FLOAT_OOB_FILL_NONE);
}
void map_rows(EncFn enc, CUtensorMap* m, const void* p, int rows, int cols, int boxrows = 64) {
  cuuint64_t d[2] = {(cuuint64_t)cols, (cuuint64_t)rows}, s[1] = {(cuuint64_t)cols * 2};
  cuuint32_t b[2] = {64, (cuuint32_t)boxrows};
  encode(enc, m, 2, p, d, s, b, CU_TENSOR_MAP_SWIZZLE_128B);
}
void map_w(EncFn enc, CUtensorMap* m, const void* p, int K, int N, int groups) {
  cuuint64_t d[3] = {64, (cuuint64_t)K, (cuuint64_t)N / 64}, s[2] = {(cuuint64_t)N * 2, 128};
  cuuint32_t b[3] = {64, 64, (cuuint32_t)groups};
  encode(enc, m, 3, p, d, s, b, CU_TENSOR_MAP_SWIZZLE_128B);
}
}

extern "C" void kernel_launch(void* const* d_in, const int* in_sizes, int n_in, void* d_out, int out_size) {
  (void)in_sizes; (void)n_in; (void)out_size;
  static EncFn enc = nullptr;
  static void *p_y, *p_h, *p_o;
  if (!enc) {
    void* fn = nullptr;
    cudaDriverEntryPointQueryResult qr;
    cudaGetDriverEntryPoint("cuTensorMapEncodeTiled", &fn, cudaEnableDefault, &qr);
    enc = (EncFn)fn;
    cudaGetSymbolAddress(&p_y, g_y);
    cudaGetSymbolAddress(&p_h, g_h);
    cudaGetSymbolAddress(&p_o, g_o);
    cudaFuncSetAttribute(fused_kernel, cudaFuncAttributeMaxDynamicSharedMemorySize, SM_TOTAL);
  }
  Params P;
  P.py = (__nv_bfloat16*)p_y; P.ph = (__nv_bfloat16*)p_h; P.po = (__nv_bfloat16*)p_o;
  map_rows(enc, &P.xa, d_in[0], S_, D_);
  map_rows(enc, &P.y, p_y, S_, D_);
  map_rows(enc, &P.h, p_h, S_, F_);
  map_rows(enc, &P.o, p_o, S_, D_);
  map_rows(enc, &P.out, d_out, S_, D_);
  map_w(enc, &P.wqkv, d_in[1], D_, 3 * D_, 2);
  map_w(enc, &P.w1a, d_in[5], D_, F_, 4);
  map_w(enc, &P.w1b, d_in[5], D_, F_, 3);
  map_w(enc, &P.w2, d_in[7], F_, D_, 2);
  map_w(enc, &P.wo, d_in[3], D_, D_, 2);
  {
    cuuint64_t d[2] = {32, 1024}, s[1] = {64};
    cuuint32_t b[2] = {32, 128};
    encode(enc, &P.wphi, 2, d_in[2], d, s, b, CU_TENSOR_MAP_SWIZZLE_64B);
  }
  P.A_x = (const __nv_bfloat16*)d_in[0];
  P.b1 = (const __nv_bfloat16*)d_in[6];
  P.b2 = (const __nv_bfloat16*)d_in[8];
  P.gate_w = (const __nv_bfloat16*)d_in[9];
  fused_kernel<<<NCTA, 512, SM_TOTAL, cudaStreamPerThread>>>(P);
}
```

```cpp
#include <cuda_runtime.h>
#include <cuda_bf16.h>
#include <cuda.h>
#include <stdint.h>

#define TIMING 0
#define OBSERVE 0
#define NOEPI 0
#define NOEPI3 0
constexpr int NS32 = 5;
#define WAITSTAT 0
#define POL_W L2_NORMAL
#define FIRSTFULL 0
#define QSKIP 0
#define MAPMODE 1
#define FTEST 0
#define GSYNC 5
#define WAITNS 50
#define EARLYREL 2
#define GSKIP 0
#define GR 2
#define WSKIP 0
#define PSPIN 0
#define PWAIT mbar_wait
#define PWARP 0
#define G2R 3
#define PUNROLL 0
#define NOHOIST 1
#define HINT 0
#define HINTOP ""
#define USE_NL 0
#define ROT_F (2 * (nn >> 1))
#define ESLEEP 1
#define EWAIT mbar_wait_sleep
#define KBSTAMP 0

namespace {

constexpr int S_ = 2048, D_ = 1024, F_ = 3584;
constexpr int NCTA = 128;
constexpr int KVP = 40;

__device__ __align__(1024) __nv_bfloat16 g_y[S_ * D_];
__device__ __align__(1024) __nv_bfloat16 g_h[S_ * F_];
__device__ __align__(1024) __nv_bfloat16 g_o[S_ * D_];
__device__ __align__(1024) float g_kv[32 * 64 * KVP];
__device__ __align__(1024) float g_gate[S_];
__device__ __align__(1024) uint32_t g_cnt[128 * 32];
constexpr int C_ZERO = 0, C_KV = 8, C_Y = 16, C_H1 = 32, C_H2 = 48, C_O = 64, C_DONE = 80, C_SYNC = 81;

constexpr uint32_t SM_RING = 0;
constexpr uint32_t SM_STG = 147456;
constexpr uint32_t SM_STGH = SM_STG + 16384;
constexpr uint32_t SM_KVZ = SM_STG + 49152;
constexpr uint32_t SM_X = 212992;
constexpr uint32_t SM_MISC = 229376;
constexpr uint32_t SM_TOTAL = 232448;
constexpr uint32_t SM_BAR = SM_MISC;
constexpr uint32_t SM_B1 = SM_MISC + 512;
constexpr uint32_t SM_GATE = SM_MISC + 2304;
constexpr uint32_t SM_B2 = SM_MISC + 2816;
constexpr uint32_t B_FULL24 = SM_BAR + 0;
constexpr uint32_t B_EMPTY24 = SM_BAR + 64;
constexpr uint32_t B_FULL32 = SM_BAR + 128;
constexpr uint32_t B_EMPTY32 = SM_BAR + 176;
constexpr uint32_t B_DUMP = SM_BAR + 224;
constexpr uint32_t B_SFREE = SM_BAR + 256;
constexpr uint32_t B_GATES = SM_BAR + 264;
constexpr uint32_t B_SLO = SM_BAR + 272;
constexpr uint32_t B_FLAG = SM_BAR + 288;
constexpr uint32_t B_WPHI = SM_BAR + 280;

struct Params {
  CUtensorMap xa, y, h, o, wqkv, wqkv32, w1a, w1b, w2, wo, wphi, out;
  const __nv_bfloat16 *A_x, *b1, *b2, *gate_w;
  __nv_bfloat16 *py, *ph, *po;
};

__device__ __forceinline__ uint32_t smem_u32(const void* p) { return (uint32_t)__cvta_generic_to_shared(p); }
__device__ __forceinline__ void mbar_init(uint32_t bar, uint32_t cnt) {
  asm volatile("mbarrier.init.shared::cta.b64 [%0], %1;" ::"r"(bar), "r"(cnt) : "memory");
}
__device__ __forceinline__ void mbar_expect_tx(uint32_t bar, uint32_t bytes) {
  asm volatile("mbarrier.arrive.expect_tx.shared::cta.b64 _, [%0], %1;" ::"r"(bar), "r"(bytes) : "memory");
}
__device__ __forceinline__ void mbar_arrive(uint32_t bar) {
  asm volatile("mbarrier.arrive.shared::cta.b64 _, [%0];" ::"r"(bar) : "memory");
}
__device__ __forceinline__ void mbar_arrive_cluster(uint32_t bar, uint32_t cta) {
  asm volatile(
      "{\n.reg .b32 ra;\nmapa.shared::cluster.u32 ra, %0, %1;\n"
      "mbarrier.arrive.shared::cluster.b64 _, [ra];\n}" ::"r"(bar), "r"(cta) : "memory");
}
__device__ __forceinline__ void mbar_wait(uint32_t bar, uint32_t parity) {
  asm volatile(
      "{\n.reg .pred p;\n.reg .u32 it;\nmov.u32 it, 0;\n"
      "MW_LOOP:\nmbarrier.try_wait.parity.shared::cta.b64 p, [%0], %1" HINTOP ";\n@p bra MW_DONE;\n"
      "add.u32 it, it, 1;\nsetp.lt.u32 p, it, 4194304;\n@p bra MW_LOOP;\ntrap;\nMW_DONE:\n}" ::"r"(bar), "r"(parity) : "memory");
}
__device__ __forceinline__ void mbar_wait_sleep(uint32_t bar, uint32_t parity) {
  asm volatile(
      "{\n.reg .pred p;\n.reg .u32 it;\nmov.u32 it, 0;\n"
      "MZ_LOOP:\nmbarrier.try_wait.parity.shared::cta.b64 p, [%0], %1, 20000;\n@p bra MZ_DONE;\n"
      "add.u32 it, it, 1;\nsetp.lt.u32 p, it, 4194304;\n@p bra MZ_LOOP;\ntrap;\nMZ_DONE:\n}" ::"r"(bar), "r"(parity) : "memory");
}
__device__ __forceinline__ void mbar_wait_nl(uint32_t bar, uint32_t parity) {
  mbar_wait(bar, parity);
  return;
  asm volatile("{\n.reg .pred p;\nMN_LOOP:\nmbarrier.try_wait.parity.shared::cta.b64 p, [%0], %1" HINTOP ";\n@!p bra MN_LOOP;\n}" ::"r"(bar), "r"(parity) : "memory");
}
__device__ __forceinline__ void mbar_spin(uint32_t bar, uint32_t parity) {
  asm volatile(
      "{\n.reg .pred p;\n.reg .u32 it;\nmov.u32 it, 0;\n"
      "MS_LOOP:\nmbarrier.test_wait.parity.shared::cta.b64 p, [%0], %1;\n@p bra MS_DONE;\n"
      "add.u32 it, it, 1;\nsetp.lt.u32 p, it, 0x10000000;\n@p bra MS_LOOP;\ntrap;\nMS_DONE:\n}" ::"r"(bar), "r"(parity) : "memory");
}
__device__ __forceinline__ bool mbar_test(uint32_t bar, uint32_t parity) {
  uint32_t ok;
  asm volatile("{\n.reg .pred p;\nmbarrier.test_wait.parity.shared::cta.b64 p, [%1], %2;\nselp.u32 %0, 1, 0, p;\n}"
               : "=r"(ok) : "r"(bar), "r"(parity) : "memory");
  return ok != 0;
}
__device__ __forceinline__ void wait_flag(const uint32_t* p, uint32_t target) {
  uint32_t it = 0;
  while (true) {
    uint32_t v;
    asm volatile("ld.acquire.gpu.global.u32 %0, [%1];" : "=r"(v) : "l"(p) : "memory");
    if ((int32_t)(v - target) >= 0) break;
    __nanosleep(WAITNS);
    if (++it > (1u << 22)) __trap();
  }
}
__device__ __forceinline__ uint32_t load_epoch() {
  uint32_t done;
  asm volatile("ld.relaxed.gpu.global.u32 %0, [%1];" : "=r"(done) : "l"(g_cnt + C_DONE * 32) : "memory");
  return done / NCTA + 1;
}
__device__ __forceinline__ void signal_flag(uint32_t* p) {
  asm volatile("red.release.gpu.global.add.u32 [%0], 1;" ::"l"(p) : "memory");
}
__device__ __forceinline__ void fence_async_all() { asm volatile("fence.proxy.async.global;" ::: "memory"); }
__device__ __forceinline__ void fence_async_smem() { asm volatile("fence.proxy.async.shared::cta;" ::: "memory"); }
constexpr uint64_t L2_NORMAL = 0x1000000000000000ull, L2_FIRST = 0x12F0000000000000ull;
__device__ __forceinline__ void tma_2d(uint32_t dst, const CUtensorMap* m, uint32_t bar, int c0, int c1, uint64_t pol) {
  asm volatile(
      "cp.async.bulk.tensor.2d.shared::cluster.global.mbarrier::complete_tx::bytes.L2::cache_hint [%0], [%1, {%3, %4}], [%2], %5;" ::"r"(dst),
      "l"(m), "r"(bar), "r"(c0), "r"(c1), "l"(pol) : "memory");
}
__device__ __forceinline__ void tma_2d_mc(uint32_t dst, const CUtensorMap* m, uint32_t bar, int c0, int c1, uint64_t pol) {
  asm volatile(
      "cp.async.bulk.tensor.2d.shared::cluster.global.mbarrier::complete_tx::bytes.multicast::cluster.L2::cache_hint [%0], [%1, {%3, "
      "%4}], [%2], %5, %6;" ::"r"(dst),
      "l"(m), "r"(bar), "r"(c0), "r"(c1), "h"((uint16_t)3), "l"(pol) : "memory");
}
__device__ __forceinline__ void tma_3d(uint32_t dst, const CUtensorMap* m, uint32_t bar, int c0, int c1, int c2, uint64_t pol) {
  asm volatile(
      "cp.async.bulk.tensor.3d.shared::cluster.global.mbarrier::complete_tx::bytes.L2::cache_hint [%0], [%1, {%3, %4, %5}], [%2], %6;" ::"r"(dst),
      "l"(m), "r"(bar), "r"(c0), "r"(c1), "r"(c2), "l"(pol) : "memory");
}
__device__ __forceinline__ void tma_store_2d(const CUtensorMap* m, uint32_t src, int c0, int c1) {
  asm volatile("cp.async.bulk.tensor.2d.global.shared::cta.bulk_group [%0, {%2, %3}], [%1];" ::"l"(m), "r"(src), "r"(c0),
               "r"(c1) : "memory");
}
__device__ __forceinline__ void prefetch_tmap(const CUtensorMap* m) {
  asm volatile("prefetch.tensormap [%0];" ::"l"(m) : "memory");
}
__device__ __forceinline__ bool elect_one() {
  uint32_t pred = 0, laneid = 0;
  asm volatile(
      "{\n.reg .b32 rx;\n.reg .pred px;\nelect.sync rx|px, %2;\n@px mov.s32 %1, 1;\nmov.s32 %0, rx;\n}\n"
      : "+r"(laneid), "+r"(pred) : "r"(0xFFFFFFFFu));
  return pred != 0;
}
__device__ __forceinline__ void wg_fence() { asm volatile("wgmma.fence.sync.aligned;" ::: "memory"); }
__device__ __forceinline__ void wg_commit() { asm volatile("wgmma.commit_group.sync.aligned;" ::: "memory"); }
template <int N>
__device__ __forceinline__ void wg_wait() { asm volatile("wgmma.wait_group.sync.aligned %0;" ::"n"(N) : "memory"); }
__device__ __forceinline__ void epi_bar() { asm volatile("bar.sync 1, 128;" ::: "memory"); }
__device__ __forceinline__ uint32_t pack_bf16(float lo, float hi) {
  uint32_t r;
  asm("cvt.rn.bf16x2.f32 %0, %1, %2;" : "=r"(r) : "f"(hi), "f"(lo));
  return r;
}
__device__ __forceinline__ float bf_lo(uint32_t v) { return __uint_as_float(v << 16); }
__device__ __forceinline__ float bf_hi(uint32_t v) { return __uint_as_float(v & 0xffff0000u); }
__device__ __forceinline__ float ex2f(float x) {
  float r;
  asm("ex2.approx.ftz.f32 %0, %1;" : "=f"(r) : "f"(x));
  return r;
}
__device__ __forceinline__ float rcpf(float x) {
  float r;
  asm("rcp.approx.ftz.f32 %0, %1;" : "=f"(r) : "f"(x));
  return r;
}
__device__ __forceinline__ float tanhf_hw(float x) {
  float r;
  asm("tanh.approx.f32 %0, %1;" : "=f"(r) : "f"(x));
  return r;
}
__device__ __forceinline__ void stsm_x4(uint32_t addr, uint32_t a, uint32_t b, uint32_t c, uint32_t d) {
  asm volatile("stmatrix.sync.aligned.m8n8.x4.shared.b16 [%0], {%1, %2, %3, %4};" ::"r"(addr), "r"(a), "r"(b), "r"(c),
               "r"(d) : "memory");
}
__device__ __forceinline__ float lds_f32(uint32_t a) {
  float v;
  asm volatile("ld.shared.f32 %0, [%1];" : "=f"(v) : "r"(a) : "memory");
  return v;
}
__device__ __forceinline__ void sts_f32(uint32_t a, float v) { asm volatile("st.shared.f32 [%0], %1;" ::"r"(a), "f"(v) : "memory"); }
__device__ __forceinline__ uint64_t make_desc(uint32_t addr, uint32_t lbo, uint32_t sbo, uint32_t swz) {
  return (uint64_t)((addr & 0x3FFFF) >> 4) | ((uint64_t)(lbo >> 4) << 16) | ((uint64_t)(sbo >> 4) << 32) |
         ((uint64_t)swz << 62);
}
template <int N>
__device__ __forceinline__ void fence_regs(float (&d)[N]) {
#pragma unroll
  for (int i = 0; i < N; i++) asm volatile("" : "+f"(d[i])::"memory");
}

__device__ __forceinline__ void wgmma_ss_n192(float (&d)[96], uint64_t da, uint64_t db, int scale_d) {
  asm volatile("{\n.reg .pred p;\nsetp.ne.b32 p, %98, 0;\n"
    "wgmma.mma_async.sync.aligned.m64n192k16.f32.bf16.bf16 "
    "{%0, %1, %2, %3, %4, %5, %6, %7, %8, %9, %10, %11, %12, %13, %14, %15, %16, %17, %18, %19, %20, %21, %22, %23, %24, %25, %26, %27, %28, %29, %30, %31, %32, %33, %34, %35, %36, %37, %38, %39, %40, %41, %42, %43, %44, %45, %46, %47, %48, %49, %50, %51, %52, %53, %54, %55, %56, %57, %58, %59, %60, %61, %62, %63, %64, %65, %66, %67, %68, %69, %70, %71, %72, %73, %74, %75, %76, %77, %78, %79, %80, %81, %82, %83, %84, %85, %86, %87, %88, %89, %90, %91, %92, %93, %94, %95}, %96, %97, p, 1, 1, 0, 1;\n}\n"
    : "+f"(d[0]), "+f"(d[1]), "+f"(d[2]), "+f"(d[3]), "+f"(d[4]), "+f"(d[5]), "+f"(d[6]), "+f"(d[7]), "+f"(d[8]), "+f"(d[9]), "+f"(d[10]), "+f"(d[11]), "+f"(d[12]), "+f"(d[13]), "+f"(d[14]), "+f"(d[15]), "+f"(d[16]), "+f"(d[17]), "+f"(d[18]), "+f"(d[19]), "+f"(d[20]), "+f"(d[21]), "+f"(d[22]), "+f"(d[23]), "+f"(d[24]), "+f"(d[25]), "+f"(d[26]), "+f"(d[27]), "+f"(d[28]), "+f"(d[29]), "+f"(d[30]), "+f"(d[31]), "+f"(d[32]), "+f"(d[33]), "+f"(d[34]), "+f"(d[35]), "+f"(d[36]), "+f"(d[37]), "+f"(d[38]), "+f"(d[39]), "+f"(d[40]), "+f"(d[41]), "+f"(d[42]), "+f"(d[43]), "+f"(d[44]), "+f"(d[45]), "+f"(d[46]), "+f"(d[47]), "+f"(d[48]), "+f"(d[49]), "+f"(d[50]), "+f"(d[51]), "+f"(d[52]), "+f"(d[53]), "+f"(d[54]), "+f"(d[55]), "+f"(d[56]), "+f"(d[57]), "+f"(d[58]), "+f"(d[59]), "+f"(d[60]), "+f"(d[61]), "+f"(d[62]), "+f"(d[63]), "+f"(d[64]), "+f"(d[65]), "+f"(d[66]), "+f"(d[67]), "+f"(d[68]), "+f"(d[69]), "+f"(d[70]), "+f"(d[71]), "+f"(d[72]), "+f"(d[73]), "+f"(d[74]), "+f"(d[75]), "+f"(d[76]), "+f"(d[77]), "+f"(d[78]), "+f"(d[79]), "+f"(d[80]), "+f"(d[81]), "+f"(d[82]), "+f"(d[83]), "+f"(d[84]), "+f"(d[85]), "+f"(d[86]), "+f"(d[87]), "+f"(d[88]), "+f"(d[89]), "+f"(d[90]), "+f"(d[91]), "+f"(d[92]), "+f"(d[93]), "+f"(d[94]), "+f"(d[95])
    : "l"(da), "l"(db), "r"(scale_d));
}
__device__ __forceinline__ void wgmma_ss_n128(float (&d)[64], uint64_t da, uint64_t db, int scale_d) {
  asm volatile("{\n.reg .pred p;\nsetp.ne.b32 p, %66, 0;\n"
    "wgmma.mma_async.sync.aligned.m64n128k16.f32.bf16.bf16 "
    "{%0, %1, %2, %3, %4, %5, %6, %7, %8, %9, %10, %11, %12, %13, %14, %15, %16, %17, %18, %19, %20, %21, %22, %23, %24, %25, %26, %27, %28, %29, %30, %31, %32, %33, %34, %35, %36, %37, %38, %39, %40, %41, %42, %43, %44, %45, %46, %47, %48, %49, %50, %51, %52, %53, %54, %55, %56, %57, %58, %59, %60, %61, %62, %63}, %64, %65, p, 1, 1, 0, 1;\n}\n"
    : "+f"(d[0]), "+f"(d[1]), "+f"(d[2]), "+f"(d[3]), "+f"(d[4]), "+f"(d[5]), "+f"(d[6]), "+f"(d[7]), "+f"(d[8]), "+f"(d[9]), "+f"(d[10]), "+f"(d[11]), "+f"(d[12]), "+f"(d[13]), "+f"(d[14]), "+f"(d[15]), "+f"(d[16]), "+f"(d[17]), "+f"(d[18]), "+f"(d[19]), "+f"(d[20]), "+f"(d[21]), "+f"(d[22]), "+f"(d[23]), "+f"(d[24]), "+f"(d[25]), "+f"(d[26]), "+f"(d[27]), "+f"(d[28]), "+f"(d[29]), "+f"(d[30]), "+f"(d[31]), "+f"(d[32]), "+f"(d[33]), "+f"(d[34]), "+f"(d[35]), "+f"(d[36]), "+f"(d[37]), "+f"(d[38]), "+f"(d[39]), "+f"(d[40]), "+f"(d[41]), "+f"(d[42]), "+f"(d[43]), "+f"(d[44]), "+f"(d[45]), "+f"(d[46]), "+f"(d[47]), "+f"(d[48]), "+f"(d[49]), "+f"(d[50]), "+f"(d[51]), "+f"(d[52]), "+f"(d[53]), "+f"(d[54]), "+f"(d[55]), "+f"(d[56]), "+f"(d[57]), "+f"(d[58]), "+f"(d[59]), "+f"(d[60]), "+f"(d[61]), "+f"(d[62]), "+f"(d[63])
    : "l"(da), "l"(db), "r"(scale_d));
}
__device__ __forceinline__ void wgmma_ss_n40_tt(float (&d)[20], uint64_t da, uint64_t db, int scale_d) {
  asm volatile("{\n.reg .pred p;\nsetp.ne.b32 p, %22, 0;\n"
    "wgmma.mma_async.sync.aligned.m64n40k16.f32.bf16.bf16 "
    "{%0, %1, %2, %3, %4, %5, %6, %7, %8, %9, %10, %11, %12, %13, %14, %15, %16, %17, %18, %19}, %20, %21, p, 1, 1, 1, 1;\n}\n"
    : "+f"(d[0]), "+f"(d[1]), "+f"(d[2]), "+f"(d[3]), "+f"(d[4]), "+f"(d[5]), "+f"(d[6]), "+f"(d[7]), "+f"(d[8]), "+f"(d[9]), "+f"(d[10]), "+f"(d[11]), "+f"(d[12]), "+f"(d[13]), "+f"(d[14]), "+f"(d[15]), "+f"(d[16]), "+f"(d[17]), "+f"(d[18]), "+f"(d[19])
    : "l"(da), "l"(db), "r"(scale_d));
}
__device__ __forceinline__ void wgmma_rs_n32(float (&d)[16], uint32_t a0, uint32_t a1, uint32_t a2, uint32_t a3, uint64_t db, int scale_d) {
  asm volatile("{\n.reg .pred p;\nsetp.ne.b32 p, %21, 0;\n"
    "wgmma.mma_async.sync.aligned.m64n32k16.f32.bf16.bf16 "
    "{%0, %1, %2, %3, %4, %5, %6, %7, %8, %9, %10, %11, %12, %13, %14, %15}, {%16, %17, %18, %19}, %20, p, 1, 1, 1;\n}\n"
    : "+f"(d[0]), "+f"(d[1]), "+f"(d[2]), "+f"(d[3]), "+f"(d[4]), "+f"(d[5]), "+f"(d[6]), "+f"(d[7]), "+f"(d[8]), "+f"(d[9]), "+f"(d[10]), "+f"(d[11]), "+f"(d[12]), "+f"(d[13]), "+f"(d[14]), "+f"(d[15])
    : "r"(a0), "r"(a1), "r"(a2), "r"(a3), "l"(db), "r"(scale_d));
}
__device__ __forceinline__ void wgmma_ss_n32_nt(float (&d)[16], uint64_t da, uint64_t db, int scale_d) {
  asm volatile("{\n.reg .pred p;\nsetp.ne.b32 p, %18, 0;\n"
    "wgmma.mma_async.sync.aligned.m64n32k16.f32.bf16.bf16 "
    "{%0, %1, %2, %3, %4, %5, %6, %7, %8, %9, %10, %11, %12, %13, %14, %15}, %16, %17, p, 1, 1, 0, 1;\n}\n"
    : "+f"(d[0]), "+f"(d[1]), "+f"(d[2]), "+f"(d[3]), "+f"(d[4]), "+f"(d[5]), "+f"(d[6]), "+f"(d[7]), "+f"(d[8]), "+f"(d[9]), "+f"(d[10]), "+f"(d[11]), "+f"(d[12]), "+f"(d[13]), "+f"(d[14]), "+f"(d[15])
    : "l"(da), "l"(db), "r"(scale_d));
}

template <int N>
struct MMA;
__device__ __forceinline__ uint64_t bdesc(uint32_t lo) { return ((uint64_t)0x40000040u << 32) | lo; }
template <>
struct MMA<256> {
  static __device__ __forceinline__ void run(float (&d)[128], uint64_t a, uint32_t b, int s, uint32_t gs) {
    wgmma_ss_n128(*reinterpret_cast<float(*)[64]>(&d[0]), a, bdesc(b), s);
    wgmma_ss_n128(*reinterpret_cast<float(*)[64]>(&d[64]), a, bdesc(b + 2 * gs), s);
  }
};
template <>
struct MMA<192> {
  static __device__ __forceinline__ void run(float (&d)[96], uint64_t a, uint32_t b, int s, uint32_t) { wgmma_ss_n192(d, a, bdesc(b), s); }
};
template <>
struct MMA<128> {
  static __device__ __forceinline__ void run(float (&d)[64], uint64_t a, uint32_t b, int s, uint32_t) { wgmma_ss_n128(d, a, bdesc(b), s); }
};

#define TSTAMP(idx)
#define TSTAMP_IF(c, idx)

__device__ __forceinline__ uint32_t offB2(int s) { return s * 16384 + (s >= 6 ? 49152 : 0); }
__device__ __forceinline__ uint32_t offA2(int s) { return 98304 + (s >> 1) * 16384 + (s >= 6 ? 32768 : 0); }
__device__ __forceinline__ uint32_t off4(int s) { return (s ^ ((s >> 1) & 1)) * 32768; }
template <int NS, int START, int COUNT, int STEP, class F>
__device__ __forceinline__ void ring_loop(F&& f) {
  int s = START;
#pragma unroll 1
  for (int i = 0; i < COUNT; i++) {
    f(s);
    s += STEP;
    if (s == NS) s = 0;
  }
}
template <int N, int KS, int NS, int START, int COUNT, bool CONT>
__device__ __forceinline__ void mainloop(float (&acc)[N / 2], uint32_t& ph, uint32_t sb, int w, int t, int ebase) {
  constexpr uint32_t FULLB = KS == 2 ? B_FULL24 : B_FULL32, EMPTYB = KS == 2 ? B_EMPTY24 : B_EMPTY32;
  constexpr bool EARLY = (EARLYREL >> (KS == 4 ? 1 : 0)) & 1;
  uint32_t dA0 = (uint32_t)make_desc(1024 + SM_RING + w * 8192, 16, 1024, 1);
  constexpr uint32_t dB0 = ((1024 + SM_RING) >> 4) | ((KS * 2048 >> 4) << 16);
  auto desc = [](uint32_t lo) { return ((uint64_t)0x40000040u << 32) | lo; };
  const bool rel = (t & 95) == 0;
  uint32_t remote;
  asm("mapa.shared::cluster.u32 %0, %1, %2;" : "=r"(remote) : "r"(sb + EMPTYB), "r"((t >> 5) & 1));
  auto release = [&](int s) {
    if (rel) asm volatile("mbarrier.arrive.shared::cluster.b64 _, [%0];" ::"r"(remote + 8 * s) : "memory");
  };
  bool ready = mbar_test(sb + FULLB + 8 * START, ph);
  bool pending = false;
  bool first = !CONT;
  int kbs = 0;
  auto step = [&](const int S) {
    const int PREV = (S + NS - 1) % NS, NEXT = (S + 1) % NS;
    if (__builtin_expect(!ready, 0)) {
      if (pending) {
        wg_wait<0>();
        release(PREV);
        pending = false;
      }
      mbar_wait_nl(sb + FULLB + 8 * S, ph);
    }
    if (KBSTAMP) { TSTAMP_IF(t == 0 && w == 0, 64 + ebase + kbs); kbs++; }
    const uint32_t da = dA0 + ((KS == 2 ? offA2(S) + (S & 1) * 64 : off4(S)) >> 4);
    const uint32_t db = dB0 + ((KS == 2 ? offB2(S) : off4(S) + 16384) >> 4);
    wg_fence();
    if constexpr (EARLY) {
      MMA<N>::run(acc, desc(da), db, first ? 0 : 1, KS * 128);
      wg_commit();
      if (pending) {
        wg_wait<1>();
        release(PREV);
      }
#pragma unroll
      for (int k = 1; k < KS; k++) MMA<N>::run(acc, desc(da + k * 2), db + k * 128, 1, KS * 128);
      wg_commit();
      if (NEXT == 0) ph ^= 1;
      ready = mbar_test(sb + FULLB + 8 * NEXT, ph);
    } else {
#pragma unroll
      for (int k = 0; k < KS; k++) MMA<N>::run(acc, desc(da + k * 2), db + k * 128, (k == 0 && first) ? 0 : 1, KS * 128);
      wg_commit();
      if (NEXT == 0) ph ^= 1;
      ready = mbar_test(sb + FULLB + 8 * NEXT, ph);
      if (pending) {
        wg_wait<1>();
        release(PREV);
      }
    }
    pending = true;
    first = false;
  };
  constexpr int LEAD = START == 0 ? 0 : (NS - START < COUNT ? NS - START : COUNT);
  constexpr int ROUNDS = (COUNT - LEAD) / NS, TAIL = (COUNT - LEAD) % NS;
#pragma unroll
  for (int i = 0; i < LEAD; i++) step(START + i);
#pragma unroll 1
  for (int r = 0; r < ROUNDS; r++) {
    dA0 = __shfl_sync(0xffffffffu, dA0, 0);
#pragma unroll
    for (int i = 0; i < NS; i++) step(i);
  }
#pragma unroll
  for (int i = 0; i < TAIL; i++) step(i);
  wg_wait<0>();
  release((START + COUNT - 1) % NS);
  fence_regs(acc);
}

__device__ __forceinline__ uint32_t bmax2(uint32_t a, uint32_t b) { uint32_t r; asm("max.bf16x2 %0, %1, %2;" : "=r"(r) : "r"(a), "r"(b)); return r; }
__device__ __forceinline__ uint32_t bmin2(uint32_t a, uint32_t b) { uint32_t r; asm("min.bf16x2 %0, %1, %2;" : "=r"(r) : "r"(a), "r"(b)); return r; }
__device__ __forceinline__ float4 lds128f(uint32_t a) {
  float4 v;
  asm volatile("ld.shared.v4.f32 {%0, %1, %2, %3}, [%4];" : "=f"(v.x), "=f"(v.y), "=f"(v.z), "=f"(v.w) : "r"(a));
  return v;
}
template <bool DEN>
__device__ __forceinline__ float hedgehog_row(const uint32_t (&w)[16], uint32_t (&out)[32], uint32_t zaddr) {
  constexpr float L2E = 1.4426950408889634f;
  uint32_t mx2[8], mn2[8];
#pragma unroll
  for (int i = 0; i < 8; i++) { mx2[i] = bmax2(w[2 * i], w[2 * i + 1]); mn2[i] = bmin2(w[2 * i], w[2 * i + 1]); }
#pragma unroll
  for (int st = 4; st > 0; st >>= 1)
#pragma unroll
    for (int i = 0; i < st; i++) { mx2[i] = bmax2(mx2[i], mx2[i + st]); mn2[i] = bmin2(mn2[i], mn2[i + st]); }
  const float a = -fmaxf(bf_lo(mx2[0]), bf_hi(mx2[0])) * L2E;
  const float b = fminf(bf_lo(mn2[0]), bf_hi(mn2[0])) * L2E;
  float den = 0.f;
#pragma unroll
  for (int sgn = 0; sgn < 2; sgn++) {
    const float mul = sgn ? -L2E : L2E, off = sgn ? b : a;
    float e[32];
#pragma unroll
    for (int i = 0; i < 16; i++) {
      e[2 * i] = ex2f(fmaf(bf_lo(w[i]), mul, off));
      e[2 * i + 1] = ex2f(fmaf(bf_hi(w[i]), mul, off));
    }
    float s0 = 0.f, s1 = 0.f, s2 = 0.f, s3 = 0.f;
#pragma unroll
    for (int i = 0; i < 8; i++) { s0 += e[4 * i]; s1 += e[4 * i + 1]; s2 += e[4 * i + 2]; s3 += e[4 * i + 3]; }
    const float r = rcpf((s0 + s1) + (s2 + s3));
    if (DEN) {
      float d0 = 0.f, d1 = 0.f, d2 = 0.f, d3 = 0.f;
#pragma unroll
      for (int i = 0; i < 8; i++) {
        const float4 z = lds128f(zaddr + sgn * 128 + i * 16);
        d0 = fmaf(e[4 * i], z.x, d0); d1 = fmaf(e[4 * i + 1], z.y, d1);
        d2 = fmaf(e[4 * i + 2], z.z, d2); d3 = fmaf(e[4 * i + 3], z.w, d3);
      }
      den = fmaf((d0 + d1) + (d2 + d3), r, den);
    }
#pragma unroll
    for (int i = 0; i < 16; i++) out[16 * sgn + i] = pack_bf16(e[2 * i] * r, e[2 * i + 1] * r);
  }
  return den;
}
__device__ __forceinline__ uint4 lds128(uint32_t a) {
  uint4 v;
  asm volatile("ld.shared.v4.u32 {%0, %1, %2, %3}, [%4];" : "=r"(v.x), "=r"(v.y), "=r"(v.z), "=r"(v.w) : "r"(a) : "memory");
  return v;
}
__device__ __forceinline__ void sts128(uint32_t a, uint32_t x, uint32_t y, uint32_t z, uint32_t w) {
  asm volatile("st.shared.v4.u32 [%0], {%1, %2, %3, %4};" ::"r"(a), "r"(x), "r"(y), "r"(z), "r"(w) : "memory");
}

__device__ __forceinline__ float gelu2(float v) {
  constexpr float C0 = 0.7978845608028654f, C1 = 0.7978845608028654f * 0.044715f;
  const float u = v * fmaf(v * v, C1, C0);
  return fmaf(v, tanhf_hw(u), v);
}
__device__ __forceinline__ uint32_t badd2(uint32_t a, uint32_t b) { uint32_t r; asm("add.rn.bf16x2 %0, %1, %2;" : "=r"(r) : "r"(a), "r"(b)); return r; }
__device__ __forceinline__ uint4 gelu8(uint4 x, uint4 b) {
  const uint32_t v0 = badd2(x.x, b.x), v1 = badd2(x.y, b.y), v2 = badd2(x.z, b.z), v3 = badd2(x.w, b.w);
  uint4 r;
  r.x = pack_bf16(gelu2(bf_lo(v0)), gelu2(bf_hi(v0)));
  r.y = pack_bf16(gelu2(bf_lo(v1)), gelu2(bf_hi(v1)));
  r.z = pack_bf16(gelu2(bf_lo(v2)), gelu2(bf_hi(v2)));
  r.w = pack_bf16(gelu2(bf_lo(v3)), gelu2(bf_hi(v3)));
  return r;
}
__device__ __forceinline__ float warp_sum(float v) {
#pragma unroll
  for (int o = 16; o > 0; o >>= 1) v += __shfl_xor_sync(0xffffffffu, v, o);
  return v;
}
#define CTA_CONTEXT()                                                                        \
  uint32_t cta_u, rank_u;                                                                    \
  asm volatile("mov.u32 %0, %%ctaid.x;" : "=r"(cta_u));                                      \
  asm volatile("mov.u32 %0, %%cluster_ctarank;" : "=r"(rank_u));                             \
  const int cta = (int)cta_u, rank = (int)rank_u, cl = cta >> 1;                             \
  const uint32_t sb = (rank_u << 24) + 1024u;      \
  const int m = CL2M(cl), nn = CL2P(cl) * 2 + rank, row0 = m * 128;                          \
  (void)cta; (void)nn; (void)row0; (void)sb;
#define CL2M(cl) (((cl) >> 4) * 4 + (((cl) >> 1) & 3))
#define CL2P(cl) ((((cl) >> 3) & 1) * 2 + ((cl) & 1))

__global__ void __cluster_dims__(2, 1, 1) __launch_bounds__(512, 1) fused_kernel(const __grid_constant__ Params P) {
  extern __shared__ __align__(1024) uint8_t smem_raw[];
  const int tid = threadIdx.x;
  const int wg = __shfl_sync(0xffffffffu, tid >> 7, 0);
  const int t = tid & 127;
  {
  CTA_CONTEXT();
  if (tid < 32) {
    if (elect_one()) {
      prefetch_tmap(&P.xa);
      prefetch_tmap(&P.wqkv32);
      if (sb != smem_u32(smem_raw)) __trap();
#pragma unroll
      for (int s = 0; s < 8; s++) mbar_init(sb + B_FULL24 + 8 * s, 1);
      asm volatile("fence.mbarrier_init.release.cluster;" ::: "memory");
      fence_async_smem();
      TSTAMP(0);
#pragma unroll
      for (int i = 0; i < 2; i++) {
        const uint32_t fb = sb + B_FULL24 + 8 * i, bb = sb + SM_RING + offB2(i);
        mbar_expect_tx(fb, (i & 1) ? 16384 : 32768);
        if (!(i & 1)) {
          tma_2d(sb + SM_RING + offA2(i), &P.xa, fb, i * 32, row0, L2_NORMAL);
          tma_2d(sb + SM_RING + offA2(i) + 8192, &P.xa, fb, i * 32, row0 + 64, L2_NORMAL);
        }
        tma_3d(bb, &P.wqkv32, fb, 0, i * 32, 16 + 2 * nn, POL_W);
        tma_3d(bb + 8192, &P.wqkv32, fb, 0, i * 32, 32 + 2 * nn, POL_W);
      }
      TSTAMP(44);
    }
    __syncwarp();
  } else if (tid == 32) {
    for (int s = 0; s < 8; s++) mbar_init(sb + B_EMPTY24 + 8 * s, 4);
    for (int s = 0; s < NS32; s++) { mbar_init(sb + B_FULL32 + 8 * s, 1); mbar_init(sb + B_EMPTY32 + 8 * s, 4); }
    for (int s = 0; s < 4; s++) mbar_init(sb + B_DUMP + 8 * s, 256);
    mbar_init(sb + B_SFREE, 128);
    mbar_init(sb + B_GATES, 128);
    mbar_init(sb + B_SLO, 2);
    mbar_init(sb + B_WPHI, 1);
    for (int s = 0; s < 5; s++) mbar_init(sb + B_FLAG + 8 * s, 1);
    asm volatile("fence.mbarrier_init.release.cluster;" ::: "memory");
  }
  }
  __syncthreads();
  asm volatile("barrier.cluster.arrive.relaxed.aligned;" ::: "memory");

  if (wg == 0) {
    asm volatile("setmaxnreg.dec.sync.aligned.u32 40;");
    CTA_CONTEXT();
    if (tid < 32 && elect_one()) {
#pragma unroll
      for (int i = 2; i < 8; i++) {
        const uint32_t fb = sb + B_FULL24 + 8 * i, bb = sb + SM_RING + offB2(i);
        mbar_expect_tx(fb, (i & 1) ? 16384 : 32768);
        if (!(i & 1)) {
          tma_2d(sb + SM_RING + offA2(i), &P.xa, fb, i * 32, row0, L2_NORMAL);
          tma_2d(sb + SM_RING + offA2(i) + 8192, &P.xa, fb, i * 32, row0 + 64, L2_NORMAL);
        }
        tma_3d(bb, &P.wqkv32, fb, 0, i * 32, 16 + 2 * nn, POL_W);
        tma_3d(bb + 8192, &P.wqkv32, fb, 0, i * 32, 32 + 2 * nn, POL_W);
      }
    }
    __syncwarp();
    asm volatile("barrier.cluster.wait.acquire.aligned;" ::: "memory");
    if ((tid >> 5) == (PWARP ^ 1) && elect_one()) {
      const uint32_t ep = load_epoch();
      wait_flag(g_cnt + (C_Y + m) * 32, ep * 8);
      mbar_arrive(sb + B_FLAG + 0);
      wait_flag(g_cnt + (C_SYNC + 16 + nn) * 32, ep * 16);
      mbar_arrive(sb + B_FLAG + 32);
      wait_flag(g_cnt + (C_H1 + m) * 32, ep * 8);
      wait_flag(g_cnt + (C_SYNC + nn) * 32, ep * 16);
      mbar_arrive(sb + B_FLAG + 8);
      wait_flag(g_cnt + (C_H2 + m) * 32, ep * 8);
      mbar_arrive(sb + B_FLAG + 16);
      wait_flag(g_cnt + (C_O + m) * 32, ep * 8);
      mbar_arrive(sb + B_FLAG + 24);
    }
    if ((tid >> 5) == PWARP && elect_one()) {
      prefetch_tmap(&P.y); prefetch_tmap(&P.wqkv); prefetch_tmap(&P.w1a); prefetch_tmap(&P.w1b); prefetch_tmap(&P.h);
      prefetch_tmap(&P.w2); prefetch_tmap(&P.o); prefetch_tmap(&P.wo);
      const int rowh = row0 + rank * 64;
      uint32_t ph24 = 0;
      {
        constexpr uint32_t F2E = B_FULL24 - B_EMPTY24;
        int k = 0;
        auto pair = [&](const int tile, const int NS, const int S) {
          const uint32_t eb = sb + B_EMPTY24 + 8 * S, fb = eb + F2E;
          const uint32_t bb = sb + SM_RING + offB2(S), ab = sb + SM_RING + offA2(S) + rank * 8192;
          const uint32_t bbytes = tile == 2 ? 12288 : 16384;
          PWAIT(eb, ph24);
          mbar_expect_tx(fb, 16384 + bbytes);
          if (tile == 0) {
            tma_3d(bb, &P.wqkv32, fb, 0, k, 16 + 2 * nn, POL_W);
            tma_3d(bb + 8192, &P.wqkv32, fb, 0, k, 32 + 2 * nn, POL_W);
          } else if (tile == 1) tma_3d(bb, &P.w1a, fb, 0, k, 7 * nn, POL_W);
          else tma_3d(bb, &P.w1b, fb, 0, k, 7 * nn + 4, POL_W);
          PWAIT(eb + 8, ph24);
          tma_2d_mc(ab, tile == 0 ? &P.xa : &P.y, fb, k, rowh, L2_NORMAL);
          mbar_expect_tx(fb + 8, bbytes);
          if (tile == 0) {
            tma_3d(bb + 16384, &P.wqkv32, fb + 8, 0, k + 32, 16 + 2 * nn, POL_W);
            tma_3d(bb + 16384 + 8192, &P.wqkv32, fb + 8, 0, k + 32, 32 + 2 * nn, POL_W);
          } else if (tile == 1) tma_3d(bb + 16384, &P.w1a, fb + 8, 0, k + 32, 7 * nn, POL_W);
          else tma_3d(bb + 16384, &P.w1b, fb + 8, 0, k + 32, 7 * nn + 4, POL_W);
          k += 64;
          if (S + 2 == NS) ph24 ^= 1;
        };
        k = 4 * 64;
        ring_loop<8, 0, 8, 2>([&](const int S) { pair(0, 8, S); });
        ring_loop<6, 0, 4, 2>([&](const int S) { pair(0, 6, S); });
        mbar_wait(sb + B_FLAG + 0, 0);
        fence_async_all();
        TSTAMP(40);
        k = 0;
        ring_loop<6, 2, 16, 2>([&](const int S) { pair(1, 6, S); });
        k = 0;
        ring_loop<6, 4, 16, 2>([&](const int S) { pair(2, 6, S); });
      }
      uint32_t ph = 1;
      int col = 0;
      auto entry = [&](const int S, const CUtensorMap* ma, const CUtensorMap* mb, int bgroup) {
        const uint32_t fb = sb + B_FULL32 + 8 * S, sa = sb + SM_RING + off4(S);
        mbar_expect_tx(fb, 32768);
        tma_2d_mc(sa + rank * 8192, ma, fb, col, rowh, POL_W);
        tma_3d(sa + 16384, mb, fb, 0, col, bgroup, POL_W);
        if (S == NS32 - 1) ph ^= 1;
      };
      asm volatile("red.relaxed.gpu.global.add.u32 [%0], 1;" ::"l"(g_cnt + (C_SYNC + 16 + nn) * 32) : "memory");
      mbar_wait(sb + B_FLAG + 32, 0);
#pragma unroll
      for (int j = 0; j < NS32; j++) {
        if (j == 0) mbar_wait(sb + B_EMPTY24 + 8 * 1, ph24);
        else if (j == 1) mbar_wait(sb + B_EMPTY24 + 8 * 3, ph24);
        else if (j == 3) mbar_wait(sb + B_EMPTY24 + 8 * 5, ph24);
        else if (j == 4) mbar_wait(sb + B_SLO, 0);
        entry(j, &P.xa, &P.wqkv, 2 * nn);
        col += 64;
      }
      ring_loop<NS32, 0, 11, 1>([&](const int S) {
        PWAIT(sb + B_EMPTY32 + 8 * S, ph);
        entry(S, &P.xa, &P.wqkv, 2 * nn);
        col += 64;
      });
      asm volatile("red.relaxed.gpu.global.add.u32 [%0], 1;" ::"l"(g_cnt + (C_SYNC + nn) * 32) : "memory");
      mbar_wait(sb + B_FLAG + 8, 0);
      fence_async_all();
      TSTAMP(41);
      const int rot = ROT_F;
      col = 448 * (rot & 7);
      int sub = 0;
      ring_loop<NS32, 1, 32, 1>([&](const int S) {
        PWAIT(sb + B_EMPTY32 + 8 * S, ph);
        entry(S, &P.h, &P.w2, 2 * nn);
        col += 64;
        if (++sub == 4) { sub = 0; col += 192; if (col == F_) col = 0; }
      });
      mbar_wait(sb + B_FLAG + 16, 0);
      fence_async_all();
      TSTAMP(42);
      col = 256 + 448 * (rot & 7);
      ring_loop<NS32, 3, 24, 1>([&](const int S) {
        PWAIT(sb + B_EMPTY32 + 8 * S, ph);
        entry(S, &P.h, &P.w2, 2 * nn);
        col += 64;
        if (++sub == 3) { sub = 0; col += 256; if (col > F_) col = 256; }
      });
      mbar_wait(sb + B_FLAG + 24, 0);
      fence_async_all();
      TSTAMP(43);
      col = 128 * (rot & 7);
      ring_loop<NS32, 2, 16, 1>([&](const int S) {
        PWAIT(sb + B_EMPTY32 + 8 * S, ph);
        entry(S, &P.o, &P.wo, 2 * nn);
        col = (col + 64) & (D_ - 1);
      });
      ring_loop<NS32, 3, NS32, 1>([&](const int S) {
        PWAIT(sb + B_EMPTY32 + 8 * S, ph);
        if (S == NS32 - 1) ph ^= 1;
      });
    }
  } else if (wg <= 2) {
    TSTAMP_IF(tid == 128, 47);
    asm volatile("setmaxnreg.inc.sync.aligned.u32 168;");
    CTA_CONTEXT();
    TSTAMP_IF(tid == 128, 48);
    asm volatile("barrier.cluster.wait.acquire.aligned;" ::: "memory");
    TSTAMP_IF(tid == 128, 49);
    const int w = wg - 1;
    const int warp = t >> 5, lane = t & 31, q = lane & 3;
    const int rloc = w * 64 + warp * 16 + (lane >> 2);
    const int srow = w * 64 + warp * 16 + ((lane >> 3) & 1) * 8 + (lane & 7);
    const uint32_t st_row = srow * 128, st_x = srow & 7, st_hi = lane >> 4;
    {
      uint32_t ph = 0;
      {
        float acc[128];
        mainloop<256, 2, 8, 0, 24, false>(acc, ph, sb, w, t, 0);
        mainloop<256, 2, 6, 0, 8, true>(acc, ph, sb, w, t, 200);
        TSTAMP_IF(t == 0, 1 + w);
        {
          uint32_t kp[32], vp[32];
#pragma unroll
          for (int i = 0; i < 32; i++) {
            vp[i] = pack_bf16(acc[64 + 2 * i], acc[64 + 2 * i + 1]);
            asm volatile("" : "+r"(vp[i]));
          }
#pragma unroll
          for (int i = 0; i < 32; i++) kp[i] = pack_bf16(acc[2 * i], acc[2 * i + 1]);
          TSTAMP_IF(t == 0 && w == 0, 430);
          mbar_wait_nl(sb + B_WPHI, 0);
          TSTAMP_IF(t == 0 && w == 0, 431);
          const uint64_t dW = make_desc(sb + SM_X, 16, 512, 2);
          float p[4][16];
          wg_fence();
#pragma unroll
          for (int h = 0; h < 4; h++) {
            wgmma_rs_n32(p[h], kp[8 * h], kp[8 * h + 1], kp[8 * h + 2], kp[8 * h + 3], dW + h * 128, 0);
            wgmma_rs_n32(p[h], kp[8 * h + 4], kp[8 * h + 5], kp[8 * h + 6], kp[8 * h + 7], dW + h * 128 + 64, 1);
          }
          wg_commit();
          TSTAMP_IF(t == 0 && w == 0, 432);
#pragma unroll
          for (int h = 0; h < 4; h++) {
            const uint32_t tb = sb + SM_STG + h * 16384 + st_row;
            stsm_x4(tb + (((0 + st_hi) ^ st_x) << 4), vp[8 * h], vp[8 * h + 1], vp[8 * h + 2], vp[8 * h + 3]);
            stsm_x4(tb + (((2 + st_hi) ^ st_x) << 4), vp[8 * h + 4], vp[8 * h + 5], vp[8 * h + 6], vp[8 * h + 7]);
          }
          TSTAMP_IF(t == 0 && w == 0, 433);
          wg_wait<0>();
          TSTAMP_IF(t == 0 && w == 0, 434);
#pragma unroll
          for (int h = 0; h < 4; h++) {
            fence_regs(p[h]);
            const uint32_t tb = sb + SM_STG + h * 16384 + st_row;
            stsm_x4(tb + (((4 + st_hi) ^ st_x) << 4), pack_bf16(p[h][0], p[h][1]), pack_bf16(p[h][2], p[h][3]),
                    pack_bf16(p[h][4], p[h][5]), pack_bf16(p[h][6], p[h][7]));
            stsm_x4(tb + (((6 + st_hi) ^ st_x) << 4), pack_bf16(p[h][8], p[h][9]), pack_bf16(p[h][10], p[h][11]),
                    pack_bf16(p[h][12], p[h][13]), pack_bf16(p[h][14], p[h][15]));
          }
          TSTAMP_IF(t == 0 && w == 0, 435);
          fence_async_smem();
          mbar_arrive(sb + B_DUMP + 0);
        }
        TSTAMP_IF(t == 0, 3 + w);
      }
      {
        float acc[128];
        mainloop<256, 2, 6, 2, 32, false>(acc, ph, sb, w, t, 201);
        TSTAMP_IF(t == 0, 5 + w);
        mbar_wait_nl(sb + B_SFREE, 0);
#pragma unroll
        for (int i = 0; i < 16; i++)
          stsm_x4(sb + SM_STG + (i >> 2) * 16384 + st_row + (((2 * (i & 3) + st_hi) ^ st_x) << 4),
                  pack_bf16(acc[8 * i], acc[8 * i + 1]), pack_bf16(acc[8 * i + 2], acc[8 * i + 3]),
                  pack_bf16(acc[8 * i + 4], acc[8 * i + 5]), pack_bf16(acc[8 * i + 6], acc[8 * i + 7]));
        mbar_arrive(sb + B_DUMP + 8);
        TSTAMP_IF(t == 0, 7 + w);
      }
      {
        float acc[96];
        mainloop<192, 2, 6, 4, 32, false>(acc, ph, sb, w, t, 202);
        TSTAMP_IF(t == 0, 9 + w);
        mbar_wait_nl(sb + B_SFREE, 1);
#pragma unroll
        for (int i = 0; i < 12; i++)
          stsm_x4(sb + SM_STGH + (i >> 2) * 16384 + st_row + (((2 * (i & 3) + st_hi) ^ st_x) << 4),
                  pack_bf16(acc[8 * i], acc[8 * i + 1]), pack_bf16(acc[8 * i + 2], acc[8 * i + 3]),
                  pack_bf16(acc[8 * i + 4], acc[8 * i + 5]), pack_bf16(acc[8 * i + 6], acc[8 * i + 7]));
        mbar_arrive(sb + B_DUMP + 16);
        TSTAMP_IF(t == 0, 11 + w);
      }
    }
    {
      uint32_t ph = 0;
      uint32_t pq[32];
      {
        float acc[64];
        mainloop<128, 4, 5, 0, 16, false>(acc, ph, sb, w, t, 48);
        TSTAMP_IF(t == 0, 13 + w);
        uint32_t qp[32];
#pragma unroll
        for (int i = 0; i < 32; i++) qp[i] = pack_bf16(acc[2 * i], acc[2 * i + 1]);
        mbar_wait_nl(sb + B_WPHI, 1);
        const uint64_t dW = make_desc(sb + SM_X, 16, 512, 2);
        float p[4][16];
        wg_fence();
#pragma unroll
        for (int h = 0; h < 4; h++) {
          wgmma_rs_n32(p[h], qp[8 * h], qp[8 * h + 1], qp[8 * h + 2], qp[8 * h + 3], dW + h * 128, 0);
          wgmma_rs_n32(p[h], qp[8 * h + 4], qp[8 * h + 5], qp[8 * h + 6], qp[8 * h + 7], dW + h * 128 + 64, 1);
        }
        wg_commit();
        wg_wait<0>();
#pragma unroll
        for (int h = 0; h < 4; h++) {
          fence_regs(p[h]);
#pragma unroll
          for (int i = 0; i < 8; i++) pq[8 * h + i] = pack_bf16(p[h][2 * i], p[h][2 * i + 1]);
        }
      }
      TSTAMP_IF(t == 0, 15 + w);
      float acc[64];
      mainloop<128, 4, 5, 1, 4, false>(acc, ph, sb, w, t, 64);
      mbar_wait_nl(sb + B_SFREE, 0);
#pragma unroll
      for (int h = 0; h < 4; h++) {
        const uint32_t tb = sb + SM_STGH + (h >> 1) * 16384 + st_row;
        stsm_x4(tb + ((((h & 1) * 4 + 0 + st_hi) ^ st_x) << 4), pq[8 * h], pq[8 * h + 1], pq[8 * h + 2], pq[8 * h + 3]);
        stsm_x4(tb + ((((h & 1) * 4 + 2 + st_hi) ^ st_x) << 4), pq[8 * h + 4], pq[8 * h + 5], pq[8 * h + 6], pq[8 * h + 7]);
      }
      mbar_arrive(sb + B_DUMP + 24);
      mainloop<128, 4, 5, 0, 52, true>(acc, ph, sb, w, t, 68);
      mbar_wait_nl(sb + B_GATES, 0);
      {
        const float s0 = 1.f - lds_f32(sb + SM_GATE + 4 * rloc), s1 = 1.f - lds_f32(sb + SM_GATE + 4 * (rloc + 8));
        const float h0 = 0.5f * s0, h1 = 0.5f * s1;
#pragma unroll
        for (int j = 0; j < 16; j++) {
          const uint32_t bb = __float_as_uint(lds_f32(sb + SM_B2 + 2 * (8 * j + 2 * q)));
          const float b0 = bf_lo(bb), b1 = bf_hi(bb);
          acc[4 * j] = fmaf(acc[4 * j], h0, s0 * b0);
          acc[4 * j + 1] = fmaf(acc[4 * j + 1], h0, s0 * b1);
          acc[4 * j + 2] = fmaf(acc[4 * j + 2], h1, s1 * b0);
          acc[4 * j + 3] = fmaf(acc[4 * j + 3], h1, s1 * b1);
        }
      }
      mainloop<128, 4, 5, 2, 16, true>(acc, ph, sb, w, t, 120);
      TSTAMP_IF(t == 0, 17 + w);
      const uint32_t stg = sb + SM_RING + w * 8192 + (st_row - w * 8192);
#pragma unroll
      for (int i = 0; i < 8; i++)
        stsm_x4(stg + (i >> 2) * 32768 + (((2 * (i & 3) + st_hi) ^ st_x) << 4), pack_bf16(acc[8 * i], acc[8 * i + 1]),
                pack_bf16(acc[8 * i + 2], acc[8 * i + 3]), pack_bf16(acc[8 * i + 4], acc[8 * i + 5]), pack_bf16(acc[8 * i + 6], acc[8 * i + 7]));
      fence_async_smem();
      if (w == 0) asm volatile("bar.sync 2, 128;" ::: "memory");
      else asm volatile("bar.sync 3, 128;" ::: "memory");
      if (t == 0) {
        tma_store_2d(&P.out, sb + SM_RING + w * 8192, 128 * nn, m * 128 + w * 64);
        tma_store_2d(&P.out, sb + SM_RING + w * 8192 + 32768, 128 * nn + 64, m * 128 + w * 64);
        asm volatile("cp.async.bulk.commit_group;" ::: "memory");
        asm volatile("cp.async.bulk.wait_group.read 0;" ::: "memory");
        TSTAMP(19 + w);
      }
    }
  } else {
    asm volatile("setmaxnreg.inc.sync.aligned.u32 136;");
    CTA_CONTEXT();
    const int warp = t >> 5, lane = t & 31, q = lane & 3;
    TSTAMP_IF(t == 0, 45);
    uint32_t ep = 0;
    if (t == 0) {
      mbar_expect_tx(sb + B_WPHI, 8192);
      tma_2d(sb + SM_X, &P.wphi, sb + B_WPHI, 0, nn * 128, L2_NORMAL);
      ep = load_epoch();
    }
    {
      const int r0 = m * 128 + nn * 16 + warp * 4;
      uint4 gw[4], xb[4][4];
#pragma unroll
      for (int u = 0; u < 4; u++)
#pragma unroll
        for (int i = 0; i < 4; i++)
          xb[u][i] = __ldg(reinterpret_cast<const uint4*>(P.A_x + (size_t)(r0 + u) * D_) + lane + 32 * i);
#pragma unroll
      for (int i = 0; i < 4; i++) gw[i] = __ldg(reinterpret_cast<const uint4*>(P.gate_w) + lane + 32 * i);
      {
        uint4* z = reinterpret_cast<uint4*>(g_kv + (size_t)nn * 4 * 64 * KVP) + m * 160;
        z[t] = make_uint4(0, 0, 0, 0);
        if (t < 32) z[128 + t] = make_uint4(0, 0, 0, 0);
      }
#pragma unroll
      for (int u = 0; u < 4; u++) {
        float sum = 0.f, dot = 0.f;
#pragma unroll
        for (int i = 0; i < 4; i++) {
          const uint32_t b[4] = {xb[u][i].x, xb[u][i].y, xb[u][i].z, xb[u][i].w};
          const uint32_t g[4] = {gw[i].x, gw[i].y, gw[i].z, gw[i].w};
#pragma unroll
          for (int k = 0; k < 4; k++) {
            sum += bf_lo(b[k]) + bf_hi(b[k]);
            dot = fmaf(bf_lo(b[k]), bf_lo(g[k]), dot);
            dot = fmaf(bf_hi(b[k]), bf_hi(g[k]), dot);
          }
        }
        const float mean = warp_sum(sum) * (1.f / D_);
        dot = warp_sum(dot);
        float var = 0.f;
#pragma unroll
        for (int i = 0; i < 4; i++) {
          const uint32_t b[4] = {xb[u][i].x, xb[u][i].y, xb[u][i].z, xb[u][i].w};
#pragma unroll
          for (int k = 0; k < 4; k++) {
            const float d0 = bf_lo(b[k]) - mean, d1 = bf_hi(b[k]) - mean;
            var = fmaf(d0, d0, var);
            var = fmaf(d1, d1, var);
          }
        }
        var = warp_sum(var) * (1.f / D_);
        const float rstd = rsqrtf(var + 1e-5f);
        uint4* dsty = reinterpret_cast<uint4*>(P.py + (size_t)(r0 + u) * D_) + lane;
#pragma unroll
        for (int i = 0; i < 4; i++) {
          const uint32_t b[4] = {xb[u][i].x, xb[u][i].y, xb[u][i].z, xb[u][i].w};
          uint32_t o[4];
#pragma unroll
          for (int k = 0; k < 4; k++) o[k] = pack_bf16((bf_lo(b[k]) - mean) * rstd, (bf_hi(b[k]) - mean) * rstd);
          dsty[32 * i] = make_uint4(o[0], o[1], o[2], o[3]);
        }
        if (lane == 0) g_gate[r0 + u] = 1.f / (1.f + __expf(-dot));
      }
      TSTAMP_IF(t == 0, 46);
      fence_async_all();
      epi_bar();
      if (t == 0) {
        signal_flag(g_cnt + (C_Y + m) * 32);
        signal_flag(g_cnt + (C_ZERO + nn) * 32);
        TSTAMP(21);
      }
    }
    asm volatile("barrier.cluster.wait.acquire.aligned;" ::: "memory");
    {
      for (int p = t; p < 224; p += 128) sts_f32(sb + SM_B1 + 4 * p, __uint_as_float(reinterpret_cast<const uint32_t*>(P.b1)[224 * nn + p]));
      if (t < 64) sts_f32(sb + SM_B2 + 4 * t, __uint_as_float(reinterpret_cast<const uint32_t*>(P.b2)[64 * nn + t]));
      if (t == 0) {
        wait_flag(g_cnt + (C_Y + m) * 32, ep * 8);
        wait_flag(g_cnt + (C_ZERO + nn) * 32, ep * 16);
      }
      epi_bar();
      sts_f32(sb + SM_GATE + 4 * t, __ldcg(g_gate + m * 128 + t));
      mbar_arrive(sb + B_GATES);
      epi_bar();
    }
    const uint32_t my_row = t * 128, my_x = t & 7;
    {
      EWAIT(sb + B_DUMP + 0, 0);
      TSTAMP_IF(t == 0, 22);
      const uint64_t dPhi = make_desc(sb + SM_X, 1024, 1024, 1);
      float kv[20];
#pragma unroll
      for (int i = 0; i < 20; i++) kv[i] = 0.f;
      float* dst = g_kv + ((size_t)(nn * 4) * 64 + warp * 16 + (lane >> 2)) * KVP;
#pragma unroll 1
      for (int h = 0; h < (NOEPI ? 0 : 4); h++) {
        const uint32_t tb = sb + SM_STG + h * 16384 + my_row;
        uint32_t pw[16];
#pragma unroll
        for (int c = 0; c < 4; c++) {
          const uint4 v = lds128(tb + (((4 + c) ^ my_x) << 4));
          pw[4 * c] = v.x; pw[4 * c + 1] = v.y; pw[4 * c + 2] = v.z; pw[4 * c + 3] = v.w;
        }
        sts128(tb + ((4 ^ my_x) << 4), 0x00003f80u, 0u, 0u, 0u);
        uint32_t phi[32];
        hedgehog_row<false>(pw, phi, 0);
        TSTAMP_IF(t == 0, 400 + 4 * h);
        if (h > 0) {
          wg_wait<0>();
          fence_regs(kv);
#pragma unroll
          for (int j = 0; j < 4; j++) {
            asm volatile("red.global.add.v2.f32 [%0], {%1, %2};" ::"l"(dst + 8 * j + 2 * q), "f"(kv[4 * j]), "f"(kv[4 * j + 1]) : "memory");
            asm volatile("red.global.add.v2.f32 [%0], {%1, %2};" ::"l"(dst + 8 * KVP + 8 * j + 2 * q), "f"(kv[4 * j + 2]), "f"(kv[4 * j + 3]) : "memory");
          }
          if (q == 0) {
            asm volatile("red.global.add.f32 [%0], %1;" ::"l"(dst + 32), "f"(kv[16]) : "memory");
            asm volatile("red.global.add.f32 [%0], %1;" ::"l"(dst + 8 * KVP + 32), "f"(kv[18]) : "memory");
          }
          dst += 64 * KVP;
        }
        epi_bar();
        TSTAMP_IF(t == 0, 401 + 4 * h);
#pragma unroll
        for (int c = 0; c < 8; c++)
          sts128(sb + SM_X + my_row + ((c ^ my_x) << 4), phi[4 * c], phi[4 * c + 1], phi[4 * c + 2], phi[4 * c + 3]);
        fence_async_smem();
        epi_bar();
        TSTAMP_IF(t == 0, 402 + 4 * h);
        const uint64_t dV = make_desc(sb + SM_STG + h * 16384, 1024, 1024, 1);
        wg_fence();
#pragma unroll
        for (int k = 0; k < 8; k++) wgmma_ss_n40_tt(kv, dPhi + k * 128, dV + k * 128, k);
        wg_commit();
        TSTAMP_IF(t == 0, 403 + 4 * h);
      }
      wg_wait<0>();
      fence_regs(kv);
      mbar_arrive(sb + B_SFREE);
#pragma unroll
      for (int j = 0; j < 4; j++) {
        asm volatile("red.global.add.v2.f32 [%0], {%1, %2};" ::"l"(dst + 8 * j + 2 * q), "f"(kv[4 * j]), "f"(kv[4 * j + 1]) : "memory");
        asm volatile("red.global.add.v2.f32 [%0], {%1, %2};" ::"l"(dst + 8 * KVP + 8 * j + 2 * q), "f"(kv[4 * j + 2]), "f"(kv[4 * j + 3]) : "memory");
      }
      if (q == 0) {
        asm volatile("red.global.add.f32 [%0], %1;" ::"l"(dst + 32), "f"(kv[16]) : "memory");
        asm volatile("red.global.add.f32 [%0], %1;" ::"l"(dst + 8 * KVP + 32), "f"(kv[18]) : "memory");
      }
      epi_bar();
      if (t == 0) {
        mbar_expect_tx(sb + B_WPHI, 8192);
        tma_2d(sb + SM_X, &P.wphi, sb + B_WPHI, 0, nn * 128, L2_NORMAL);
        signal_flag(g_cnt + (C_KV + nn) * 32);
        TSTAMP(23);
      }
    }
    {
      const uint4 b = lds128(sb + SM_B1 + 16 * lane);
      __nv_bfloat16* base = P.ph + (size_t)(m * 128 + warp * 32) * F_ + 448 * nn + 8 * lane;
      const uint32_t src = sb + SM_STG + (lane >> 3) * 16384 + warp * 32 * 128;
      EWAIT(sb + B_DUMP + 8, 0);
      TSTAMP_IF(t == 0, 24);
#pragma unroll 1
      for (int r = 0; r < (NOEPI ? 0 : 32); r += GR) {
        uint4 x[GR];
#pragma unroll
        for (int u = 0; u < GR; u++) x[u] = lds128(src + (r + u) * 128 + (((lane & 7) ^ ((r + u) & 7)) << 4));
#pragma unroll
        for (int u = 0; u < GR; u++) *reinterpret_cast<uint4*>(base + (size_t)(r + u) * F_) = gelu8(x[u], b);
      }
      mbar_arrive(sb + B_SFREE);
      fence_async_all();
      epi_bar();
      if (t < 2) mbar_arrive_cluster(sb + B_SLO, t);
      if (t == 0) { signal_flag(g_cnt + (C_H1 + m) * 32); TSTAMP(25); }
    }
    {
      uint4 b[3];
      int ro[3], co[3];
#pragma unroll
      for (int u = 0; u < 3; u++) {
        const int L = u * 32 + lane;
        ro[u] = L / 24;
        co[u] = L % 24;
        b[u] = lds128(sb + SM_B1 + 512 + 16 * co[u]);
      }
      __nv_bfloat16* base = P.ph + (size_t)(m * 128 + warp * 32) * F_ + 448 * nn + 256;
      EWAIT(sb + B_DUMP + 16, 0);
      TSTAMP_IF(t == 0, 26);
#pragma unroll 1
      for (int r = 0; r < (NOEPI ? 0 : 32); r += 4) {
        uint4 x[3];
#pragma unroll
        for (int u = 0; u < 3; u++) {
          const int row = warp * 32 + r + ro[u];
          x[u] = lds128(sb + SM_STGH + (co[u] >> 3) * 16384 + row * 128 + (((co[u] & 7) ^ (row & 7)) << 4));
        }
#pragma unroll
        for (int u = 0; u < 3; u++) *reinterpret_cast<uint4*>(base + (size_t)(r + ro[u]) * F_ + 8 * co[u]) = gelu8(x[u], b[u]);
      }
      mbar_arrive(sb + B_SFREE);
      fence_async_all();
      epi_bar();
      if (t == 0) { signal_flag(g_cnt + (C_H2 + m) * 32); TSTAMP(27); }
    }
    {
      constexpr uint32_t SM_Z = SM_B1, SM_DEN = SM_B1 + 1024;
      if (t == 0) wait_flag(g_cnt + (C_KV + nn) * 32, ep * 16);
      epi_bar();
      {
        const float* ksrc = g_kv + (size_t)(nn * 4) * 64 * KVP;
        const float z0 = __ldcg(ksrc + t * KVP + 32), z1 = __ldcg(ksrc + (128 + t) * KVP + 32);
#pragma unroll
        for (int hp = 0; hp < 2; hp++) {
          float4 kvv[8];
#pragma unroll
          for (int u = 0; u < 8; u++) {
            const int idx = (hp * 8 + u) * 128 + t;
            kvv[u] = __ldcg(reinterpret_cast<const float4*>(ksrc + (idx >> 3) * KVP + 4 * (idx & 7)));
          }
#pragma unroll
          for (int u = 0; u < 8; u++) {
            const int idx = (hp * 8 + u) * 128 + t, f = idx >> 3, c4 = idx & 7;
            asm volatile("st.shared.v2.u32 [%0], {%1, %2};" ::"r"(sb + SM_KVZ + f * 64 + (((c4 >> 1) ^ ((f >> 1) & 3)) << 4) + (c4 & 1) * 8),
                         "r"(pack_bf16(kvv[u].x, kvv[u].y)), "r"(pack_bf16(kvv[u].z, kvv[u].w)) : "memory");
          }
        }
        sts_f32(sb + SM_Z + 4 * t, bf_lo(pack_bf16(z0, z0)));
        sts_f32(sb + SM_Z + 4 * (128 + t), bf_lo(pack_bf16(z1, z1)));
      }
      EWAIT(sb + B_DUMP + 24, 0);
      epi_bar();
      TSTAMP_IF(t == 0, 28);
#pragma unroll 1
      for (int h = 0; h < ((NOEPI || NOEPI3) ? 0 : 4); h++) {
        const uint32_t tb = sb + SM_STGH + (h >> 1) * 16384 + my_row;
        uint32_t pw[16];
#pragma unroll
        for (int c = 0; c < 4; c++) {
          const uint4 v = lds128(tb + ((((h & 1) * 4 + c) ^ my_x) << 4));
          pw[4 * c] = v.x; pw[4 * c + 1] = v.y; pw[4 * c + 2] = v.z; pw[4 * c + 3] = v.w;
        }
        TSTAMP_IF(t == 0 && h == 1, 420);
        uint32_t phi[32];
        const float den = hedgehog_row<true>(pw, phi, sb + SM_Z + h * 256);
        TSTAMP_IF(t == 0 && h == 1, 421);
        epi_bar();
        TSTAMP_IF(t == 0 && h == 1, 422);
#pragma unroll
        for (int c = 0; c < 8; c++)
          sts128(sb + SM_X + my_row + ((c ^ my_x) << 4), phi[4 * c], phi[4 * c + 1], phi[4 * c + 2], phi[4 * c + 3]);
        sts_f32(sb + SM_DEN + 4 * t, lds_f32(sb + SM_GATE + 4 * t) * rcpf(den + 1e-6f));
        TSTAMP_IF(t == 0 && h == 1, 423);
        fence_async_smem();
        epi_bar();
        TSTAMP_IF(t == 0 && h == 1, 424);
        const uint64_t dK = make_desc(sb + SM_KVZ + h * 4096, 16, 512, 2);
        const uint64_t dQ = make_desc(sb + SM_X, 16, 1024, 1);
        float nd[2][16];
        wg_fence();
#pragma unroll
        for (int hf = 0; hf < 2; hf++)
#pragma unroll
          for (int k = 0; k < ((QSKIP & 2) ? 1 : 4); k++) wgmma_ss_n32_nt(nd[hf], dQ + hf * 512 + k * 2, dK + k * 64, k);
        wg_commit();
        TSTAMP_IF(t == 0 && h == 1, 425);
        wg_wait<0>();
        TSTAMP_IF(t == 0 && h == 1, 426);
#pragma unroll
        for (int hf = 0; hf < 2; hf++) {
          fence_regs(nd[hf]);
          const int rl = hf * 64 + warp * 16 + (lane >> 2);
          const float f0 = lds_f32(sb + SM_DEN + 4 * rl), f1 = lds_f32(sb + SM_DEN + 4 * (rl + 8));
          const int srow = hf * 64 + warp * 16 + ((lane >> 3) & 1) * 8 + (lane & 7);
          const uint32_t ob = sb + SM_STGH + (h >> 1) * 16384 + srow * 128;
#pragma unroll
          for (int c = 0; c < 2; c++)
            stsm_x4(ob + ((((h & 1) * 4 + 2 * c + (lane >> 4)) ^ (srow & 7)) << 4),
                    pack_bf16(nd[hf][8 * c] * f0, nd[hf][8 * c + 1] * f0), pack_bf16(nd[hf][8 * c + 2] * f1, nd[hf][8 * c + 3] * f1),
                    pack_bf16(nd[hf][8 * c + 4] * f0, nd[hf][8 * c + 5] * f0), pack_bf16(nd[hf][8 * c + 6] * f1, nd[hf][8 * c + 7] * f1));
        }
        TSTAMP_IF(t == 0 && h == 1, 427);
        TSTAMP_IF(t == 0 && h == 0, 419);
      }
      fence_async_smem();
      epi_bar();
      if (t == 0) {
        if (!(QSKIP & 4)) {
#pragma unroll
          for (int i = 0; i < 4; i++)
            tma_store_2d(&P.o, sb + SM_STGH + (i >> 1) * 16384 + (i & 1) * 8192, 128 * nn + (i >> 1) * 64, m * 128 + (i & 1) * 64);
          asm volatile("cp.async.bulk.commit_group;" ::: "memory");
          asm volatile("cp.async.bulk.wait_group 0;" ::: "memory");
        }
        signal_flag(g_cnt + (C_O + m) * 32);
        TSTAMP(29);
        asm volatile("red.relaxed.gpu.global.add.u32 [%0], 1;" ::"l"(g_cnt + C_DONE * 32) : "memory");
      }
    }
  }
}

typedef CUresult (*EncFn)(CUtensorMap*, CUtensorMapDataType, cuuint32_t, void*, const cuuint64_t*, const cuuint64_t*,
                          const cuuint32_t*, const cuuint32_t*, CUtensorMapInterleave, CUtensorMapSwizzle,
                          CUtensorMapL2promotion, CUtensorMapFloatOOBfill);

void encode(EncFn enc, CUtensorMap* m, int rank, const void* p, const cuuint64_t* dims, const cuuint64_t* strides,
            const cuuint32_t* box, CUtensorMapSwizzle swz) {
  cuuint32_t e[5] = {1, 1, 1, 1, 1};
  enc(m, CU_TENSOR_MAP_DATA_TYPE_BFLOAT16, rank, const_cast<void*>(p), dims, strides, box, e, CU_TENSOR_MAP_INTERLEAVE_NONE, swz,
      CU_TENSOR_MAP_L2_PROMOTION_L2_256B, CU_TENSOR_MAP_FLOAT_OOB_FILL_NONE);
}
void map_rows(EncFn enc, CUtensorMap* m, const void* p, int rows, int cols, int boxrows = 64) {
  cuuint64_t d[2] = {(cuuint64_t)cols, (cuuint64_t)rows}, s[1] = {(cuuint64_t)cols * 2};
  cuuint32_t b[2] = {64, (cuuint32_t)boxrows};
  encode(enc, m, 2, p, d, s, b, CU_TENSOR_MAP_SWIZZLE_128B);
}
void map_w(EncFn enc, CUtensorMap* m, const void* p, int K, int N, int groups, int boxk = 64) {
  cuuint64_t d[3] = {64, (cuuint64_t)K, (cuuint64_t)N / 64}, s[2] = {(cuuint64_t)N * 2, 128};
  cuuint32_t b[3] = {64, (cuuint32_t)boxk, (cuuint32_t)groups};
  encode(enc, m, 3, p, d, s, b, CU_TENSOR_MAP_SWIZZLE_128B);
}
}

extern "C" void kernel_launch(void* const* d_in, const int* in_sizes, int n_in, void* d_out, int out_size) {
  (void)in_sizes; (void)n_in; (void)out_size;
  static EncFn enc = nullptr;
  static void *p_y, *p_h, *p_o;
  if (!enc) {
    void* fn = nullptr;
    cudaDriverEntryPointQueryResult qr;
    cudaGetDriverEntryPoint("cuTensorMapEncodeTiled", &fn, cudaEnableDefault, &qr);
    enc = (EncFn)fn;
    cudaGetSymbolAddress(&p_y, g_y);
    cudaGetSymbolAddress(&p_h, g_h);
    cudaGetSymbolAddress(&p_o, g_o);
    cudaFuncSetAttribute(fused_kernel, cudaFuncAttributeMaxDynamicSharedMemorySize, SM_TOTAL);
  }
  Params P;
  P.py = (__nv_bfloat16*)p_y; P.ph = (__nv_bfloat16*)p_h; P.po = (__nv_bfloat16*)p_o;
  map_rows(enc, &P.xa, d_in[0], S_, D_);
  map_rows(enc, &P.y, p_y, S_, D_);
  map_rows(enc, &P.h, p_h, S_, F_);
  map_rows(enc, &P.o, p_o, S_, D_);
  map_rows(enc, &P.out, d_out, S_, D_);
  map_w(enc, &P.wqkv, d_in[1], D_, 3 * D_, 2);
  map_w(enc, &P.wqkv32, d_in[1], D_, 3 * D_, 2, 32);
  map_w(enc, &P.w1a, d_in[5], D_, F_, 4, 32);
  map_w(enc, &P.w1b, d_in[5], D_, F_, 3, 32);
  map_w(enc, &P.w2, d_in[7], F_, D_, 2);
  map_w(enc, &P.wo, d_in[3], D_, D_, 2);
  {
    cuuint64_t d[2] = {32, 1024}, s[1] = {64};
    cuuint32_t b[2] = {32, 128};
    encode(enc, &P.wphi, 2, d_in[2], d, s, b, CU_TENSOR_MAP_SWIZZLE_64B);
  }
  P.A_x = (const __nv_bfloat16*)d_in[0];
  P.b1 = (const __nv_bfloat16*)d_in[6];
  P.b2 = (const __nv_bfloat16*)d_in[8];
  P.gate_w = (const __nv_bfloat16*)d_in[9];
  fused_kernel<<<NCTA, 512, SM_TOTAL, cudaStreamPerThread>>>(P);
}
```

```cpp
#include <cuda_runtime.h>
#include <cuda_bf16.h>
#include <cuda.h>
#include <stdint.h>

#define TIMING 0
#define OBSERVE 0
#define NOEPI 0
#define NOEPI3 0
constexpr int NS32 = 5;
#define WAITSTAT 0
#define POL_W L2_NORMAL
#define FIRSTFULL 0
#define QSKIP 0
#define MAPMODE 1
#define FTEST 0
#define GSYNC 5
#define WAITNS 50
#define EARLYREL 2
#define GSKIP 0
#define GR 2
#define WSKIP 0
#define PSPIN 0
#define PWAIT mbar_wait
#define PWARP 2
#define G2R 3
#define PUNROLL 0
#define NOHOIST 1
#define HINT 0
#define HINTOP ""
#define USE_NL 0
#define ROT_F (2 * (nn >> 1))
#define ESLEEP 1
#define EWAIT mbar_wait_sleep
#define NOA 0
#define PROMO_W CU_TENSOR_MAP_L2_PROMOTION_L2_256B
#define PROMO_A CU_TENSOR_MAP_L2_PROMOTION_L2_256B
#define BIASINIT 1
#define STMODE 0
#define STH(p, v) (*(p) = (v))
#define BSTAMP 0
#define BST(i)
#define KBSTAMP 0

namespace {

constexpr int S_ = 2048, D_ = 1024, F_ = 3584;
constexpr int NCTA = 128;
constexpr int KVP = 40;

__device__ __align__(1024) __nv_bfloat16 g_y[S_ * D_];
__device__ __align__(1024) __nv_bfloat16 g_h[S_ * F_];
__device__ __align__(1024) __nv_bfloat16 g_o[S_ * D_];
__device__ __align__(1024) float g_kv[32 * 64 * KVP];
__device__ __align__(1024) float g_gate[S_];
__device__ __align__(1024) uint32_t g_cnt[128 * 32];
constexpr int C_ZERO = 0, C_KV = 8, C_Y = 16, C_H1 = 32, C_H2 = 48, C_O = 64, C_DONE = 80, C_SYNC = 81;

constexpr uint32_t SM_RING = 0;
constexpr uint32_t SM_STG = 147456;
constexpr uint32_t SM_STGH = SM_STG + 16384;
constexpr uint32_t SM_KVZ = SM_STG + 49152;
constexpr uint32_t SM_X = 212992;
constexpr uint32_t SM_MISC = 229376;
constexpr uint32_t SM_TOTAL = 232448;
constexpr uint32_t SM_BAR = SM_MISC;
constexpr uint32_t SM_B1 = SM_MISC + 512;
constexpr uint32_t SM_GATE = SM_MISC + 2304;
constexpr uint32_t SM_B2 = SM_MISC + 2816;
constexpr uint32_t B_FULL24 = SM_BAR + 0;
constexpr uint32_t B_EMPTY24 = SM_BAR + 64;
constexpr uint32_t B_FULL32 = SM_BAR + 128;
constexpr uint32_t B_EMPTY32 = SM_BAR + 176;
constexpr uint32_t B_DUMP = SM_BAR + 224;
constexpr uint32_t B_SFREE = SM_BAR + 256;
constexpr uint32_t B_GATES = SM_BAR + 264;
constexpr uint32_t B_SLO = SM_BAR + 272;
constexpr uint32_t B_FLAG = SM_BAR + 288;
constexpr uint32_t B_WPHI = SM_BAR + 280;

struct Params {
  CUtensorMap xa, y, h, o, wqkv, wqkv32, w1a, w1b, w2, wo, wphi, out;
  const __nv_bfloat16 *A_x, *b1, *b2, *gate_w;
  __nv_bfloat16 *py, *ph, *po;
};

__device__ __forceinline__ uint32_t smem_u32(const void* p) { return (uint32_t)__cvta_generic_to_shared(p); }
__device__ __forceinline__ void mbar_init(uint32_t bar, uint32_t cnt) {
  asm volatile("mbarrier.init.shared::cta.b64 [%0], %1;" ::"r"(bar), "r"(cnt) : "memory");
}
__device__ __forceinline__ void mbar_expect_tx(uint32_t bar, uint32_t bytes) {
  asm volatile("mbarrier.arrive.expect_tx.shared::cta.b64 _, [%0], %1;" ::"r"(bar), "r"(bytes) : "memory");
}
__device__ __forceinline__ void mbar_arrive(uint32_t bar) {
  asm volatile("mbarrier.arrive.shared::cta.b64 _, [%0];" ::"r"(bar) : "memory");
}
__device__ __forceinline__ void mbar_arrive_cluster(uint32_t bar, uint32_t cta) {
  asm volatile(
      "{\n.reg .b32 ra;\nmapa.shared::cluster.u32 ra, %0, %1;\n"
      "mbarrier.arrive.shared::cluster.b64 _, [ra];\n}" ::"r"(bar), "r"(cta) : "memory");
}
__device__ __forceinline__ void mbar_wait(uint32_t bar, uint32_t parity) {
  asm volatile(
      "{\n.reg .pred p;\n.reg .u32 it;\nmov.u32 it, 0;\n"
      "MW_LOOP:\nmbarrier.try_wait.parity.shared::cta.b64 p, [%0], %1" HINTOP ";\n@p bra MW_DONE;\n"
      "add.u32 it, it, 1;\nsetp.lt.u32 p, it, 4194304;\n@p bra MW_LOOP;\ntrap;\nMW_DONE:\n}" ::"r"(bar), "r"(parity) : "memory");
}
__device__ __forceinline__ void mbar_wait_sleep(uint32_t bar, uint32_t parity) {
  asm volatile(
      "{\n.reg .pred p;\n.reg .u32 it;\nmov.u32 it, 0;\n"
      "MZ_LOOP:\nmbarrier.try_wait.parity.shared::cta.b64 p, [%0], %1, 20000;\n@p bra MZ_DONE;\n"
      "add.u32 it, it, 1;\nsetp.lt.u32 p, it, 4194304;\n@p bra MZ_LOOP;\ntrap;\nMZ_DONE:\n}" ::"r"(bar), "r"(parity) : "memory");
}
__device__ __forceinline__ void mbar_wait_nl(uint32_t bar, uint32_t parity) {
  mbar_wait(bar, parity);
  return;
  asm volatile("{\n.reg .pred p;\nMN_LOOP:\nmbarrier.try_wait.parity.shared::cta.b64 p, [%0], %1" HINTOP ";\n@!p bra MN_LOOP;\n}" ::"r"(bar), "r"(parity) : "memory");
}
__device__ __forceinline__ void mbar_spin(uint32_t bar, uint32_t parity) {
  asm volatile(
      "{\n.reg .pred p;\n.reg .u32 it;\nmov.u32 it, 0;\n"
      "MS_LOOP:\nmbarrier.test_wait.parity.shared::cta.b64 p, [%0], %1;\n@p bra MS_DONE;\n"
      "add.u32 it, it, 1;\nsetp.lt.u32 p, it, 0x10000000;\n@p bra MS_LOOP;\ntrap;\nMS_DONE:\n}" ::"r"(bar), "r"(parity) : "memory");
}
__device__ __forceinline__ bool mbar_test(uint32_t bar, uint32_t parity) {
  uint32_t ok;
  asm volatile("{\n.reg .pred p;\nmbarrier.test_wait.parity.shared::cta.b64 p, [%1], %2;\nselp.u32 %0, 1, 0, p;\n}"
               : "=r"(ok) : "r"(bar), "r"(parity) : "memory");
  return ok != 0;
}
__device__ __forceinline__ void wait_flag(const uint32_t* p, uint32_t target) {
  uint32_t it = 0;
  while (true) {
    uint32_t v;
    asm volatile("ld.acquire.gpu.global.u32 %0, [%1];" : "=r"(v) : "l"(p) : "memory");
    if ((int32_t)(v - target) >= 0) break;
    __nanosleep(WAITNS);
    if (++it > (1u << 22)) __trap();
  }
}
__device__ __forceinline__ uint32_t load_epoch() {
  uint32_t done;
  asm volatile("ld.relaxed.gpu.global.u32 %0, [%1];" : "=r"(done) : "l"(g_cnt + C_DONE * 32) : "memory");
  return done / NCTA + 1;
}
__device__ __forceinline__ void signal_flag(uint32_t* p) {
  asm volatile("red.release.gpu.global.add.u32 [%0], 1;" ::"l"(p) : "memory");
}
__device__ __forceinline__ void fence_async_all() { asm volatile("fence.proxy.async.global;" ::: "memory"); }
__device__ __forceinline__ void fence_async_smem() { asm volatile("fence.proxy.async.shared::cta;" ::: "memory"); }
constexpr uint64_t L2_NORMAL = 0x1000000000000000ull, L2_FIRST = 0x12F0000000000000ull;
__device__ __forceinline__ void tma_2d(uint32_t dst, const CUtensorMap* m, uint32_t bar, int c0, int c1, uint64_t pol) {
  asm volatile(
      "cp.async.bulk.tensor.2d.shared::cluster.global.mbarrier::complete_tx::bytes.L2::cache_hint [%0], [%1, {%3, %4}], [%2], %5;" ::"r"(dst),
      "l"(m), "r"(bar), "r"(c0), "r"(c1), "l"(pol) : "memory");
}
__device__ __forceinline__ void tma_2d_mc(uint32_t dst, const CUtensorMap* m, uint32_t bar, int c0, int c1, uint64_t pol) {
  asm volatile(
      "cp.async.bulk.tensor.2d.shared::cluster.global.mbarrier::complete_tx::bytes.multicast::cluster.L2::cache_hint [%0], [%1, {%3, "
      "%4}], [%2], %5, %6;" ::"r"(dst),
      "l"(m), "r"(bar), "r"(c0), "r"(c1), "h"((uint16_t)3), "l"(pol) : "memory");
}
__device__ __forceinline__ void tma_3d(uint32_t dst, const CUtensorMap* m, uint32_t bar, int c0, int c1, int c2, uint64_t pol) {
  asm volatile(
      "cp.async.bulk.tensor.3d.shared::cluster.global.mbarrier::complete_tx::bytes.L2::cache_hint [%0], [%1, {%3, %4, %5}], [%2], %6;" ::"r"(dst),
      "l"(m), "r"(bar), "r"(c0), "r"(c1), "r"(c2), "l"(pol) : "memory");
}
__device__ __forceinline__ void tma_store_2d(const CUtensorMap* m, uint32_t src, int c0, int c1) {
  asm volatile("cp.async.bulk.tensor.2d.global.shared::cta.bulk_group [%0, {%2, %3}], [%1];" ::"l"(m), "r"(src), "r"(c0),
               "r"(c1) : "memory");
}
__device__ __forceinline__ void prefetch_tmap(const CUtensorMap* m) {
  asm volatile("prefetch.tensormap [%0];" ::"l"(m) : "memory");
}
__device__ __forceinline__ bool elect_one() {
  uint32_t pred = 0, laneid = 0;
  asm volatile(
      "{\n.reg .b32 rx;\n.reg .pred px;\nelect.sync rx|px, %2;\n@px mov.s32 %1, 1;\nmov.s32 %0, rx;\n}\n"
      : "+r"(laneid), "+r"(pred) : "r"(0xFFFFFFFFu));
  return pred != 0;
}
__device__ __forceinline__ void wg_fence() { asm volatile("wgmma.fence.sync.aligned;" ::: "memory"); }
__device__ __forceinline__ void wg_commit() { asm volatile("wgmma.commit_group.sync.aligned;" ::: "memory"); }
template <int N>
__device__ __forceinline__ void wg_wait() { asm volatile("wgmma.wait_group.sync.aligned %0;" ::"n"(N) : "memory"); }
__device__ __forceinline__ void epi_bar() { asm volatile("bar.sync 1, 128;" ::: "memory"); }
__device__ __forceinline__ uint32_t pack_bf16(float lo, float hi) {
  uint32_t r;
  asm("cvt.rn.bf16x2.f32 %0, %1, %2;" : "=r"(r) : "f"(hi), "f"(lo));
  return r;
}
__device__ __forceinline__ float bf_lo(uint32_t v) { return __uint_as_float(v << 16); }
__device__ __forceinline__ float bf_hi(uint32_t v) { return __uint_as_float(v & 0xffff0000u); }
__device__ __forceinline__ float ex2f(float x) {
  float r;
  asm("ex2.approx.ftz.f32 %0, %1;" : "=f"(r) : "f"(x));
  return r;
}
__device__ __forceinline__ float rcpf(float x) {
  float r;
  asm("rcp.approx.ftz.f32 %0, %1;" : "=f"(r) : "f"(x));
  return r;
}
__device__ __forceinline__ float tanhf_hw(float x) {
  float r;
  asm("tanh.approx.f32 %0, %1;" : "=f"(r) : "f"(x));
  return r;
}
__device__ __forceinline__ void stsm_x4(uint32_t addr, uint32_t a, uint32_t b, uint32_t c, uint32_t d) {
  asm volatile("stmatrix.sync.aligned.m8n8.x4.shared.b16 [%0], {%1, %2, %3, %4};" ::"r"(addr), "r"(a), "r"(b), "r"(c),
               "r"(d) : "memory");
}
__device__ __forceinline__ float lds_f32(uint32_t a) {
  float v;
  asm volatile("ld.shared.f32 %0, [%1];" : "=f"(v) : "r"(a) : "memory");
  return v;
}
__device__ __forceinline__ void sts_f32(uint32_t a, float v) { asm volatile("st.shared.f32 [%0], %1;" ::"r"(a), "f"(v) : "memory"); }
__device__ __forceinline__ uint64_t make_desc(uint32_t addr, uint32_t lbo, uint32_t sbo, uint32_t swz) {
  return (uint64_t)((addr & 0x3FFFF) >> 4) | ((uint64_t)(lbo >> 4) << 16) | ((uint64_t)(sbo >> 4) << 32) |
         ((uint64_t)swz << 62);
}
template <int N>
__device__ __forceinline__ void fence_regs(float (&d)[N]) {
#pragma unroll
  for (int i = 0; i < N; i++) asm volatile("" : "+f"(d[i])::"memory");
}

__device__ __forceinline__ void wgmma_ss_n192(float (&d)[96], uint64_t da, uint64_t db, int scale_d) {
  asm volatile("{\n.reg .pred p;\nsetp.ne.b32 p, %98, 0;\n"
    "wgmma.mma_async.sync.aligned.m64n192k16.f32.bf16.bf16 "
    "{%0, %1, %2, %3, %4, %5, %6, %7, %8, %9, %10, %11, %12, %13, %14, %15, %16, %17, %18, %19, %20, %21, %22, %23, %24, %25, %26, %27, %28, %29, %30, %31, %32, %33, %34, %35, %36, %37, %38, %39, %40, %41, %42, %43, %44, %45, %46, %47, %48, %49, %50, %51, %52, %53, %54, %55, %56, %57, %58, %59, %60, %61, %62, %63, %64, %65, %66, %67, %68, %69, %70, %71, %72, %73, %74, %75, %76, %77, %78, %79, %80, %81, %82, %83, %84, %85, %86, %87, %88, %89, %90, %91, %92, %93, %94, %95}, %96, %97, p, 1, 1, 0, 1;\n}\n"
    : "+f"(d[0]), "+f"(d[1]), "+f"(d[2]), "+f"(d[3]), "+f"(d[4]), "+f"(d[5]), "+f"(d[6]), "+f"(d[7]), "+f"(d[8]), "+f"(d[9]), "+f"(d[10]), "+f"(d[11]), "+f"(d[12]), "+f"(d[13]), "+f"(d[14]), "+f"(d[15]), "+f"(d[16]), "+f"(d[17]), "+f"(d[18]), "+f"(d[19]), "+f"(d[20]), "+f"(d[21]), "+f"(d[22]), "+f"(d[23]), "+f"(d[24]), "+f"(d[25]), "+f"(d[26]), "+f"(d[27]), "+f"(d[28]), "+f"(d[29]), "+f"(d[30]), "+f"(d[31]), "+f"(d[32]), "+f"(d[33]), "+f"(d[34]), "+f"(d[35]), "+f"(d[36]), "+f"(d[37]), "+f"(d[38]), "+f"(d[39]), "+f"(d[40]), "+f"(d[41]), "+f"(d[42]), "+f"(d[43]), "+f"(d[44]), "+f"(d[45]), "+f"(d[46]), "+f"(d[47]), "+f"(d[48]), "+f"(d[49]), "+f"(d[50]), "+f"(d[51]), "+f"(d[52]), "+f"(d[53]), "+f"(d[54]), "+f"(d[55]), "+f"(d[56]), "+f"(d[57]), "+f"(d[58]), "+f"(d[59]), "+f"(d[60]), "+f"(d[61]), "+f"(d[62]), "+f"(d[63]), "+f"(d[64]), "+f"(d[65]), "+f"(d[66]), "+f"(d[67]), "+f"(d[68]), "+f"(d[69]), "+f"(d[70]), "+f"(d[71]), "+f"(d[72]), "+f"(d[73]), "+f"(d[74]), "+f"(d[75]), "+f"(d[76]), "+f"(d[77]), "+f"(d[78]), "+f"(d[79]), "+f"(d[80]), "+f"(d[81]), "+f"(d[82]), "+f"(d[83]), "+f"(d[84]), "+f"(d[85]), "+f"(d[86]), "+f"(d[87]), "+f"(d[88]), "+f"(d[89]), "+f"(d[90]), "+f"(d[91]), "+f"(d[92]), "+f"(d[93]), "+f"(d[94]), "+f"(d[95])
    : "l"(da), "l"(db), "r"(scale_d));
}
__device__ __forceinline__ void wgmma_ss_n128(float (&d)[64], uint64_t da, uint64_t db, int scale_d) {
  asm volatile("{\n.reg .pred p;\nsetp.ne.b32 p, %66, 0;\n"
    "wgmma.mma_async.sync.aligned.m64n128k16.f32.bf16.bf16 "
    "{%0, %1, %2, %3, %4, %5, %6, %7, %8, %9, %10, %11, %12, %13, %14, %15, %16, %17, %18, %19, %20, %21, %22, %23, %24, %25, %26, %27, %28, %29, %30, %31, %32, %33, %34, %35, %36, %37, %38, %39, %40, %41, %42, %43, %44, %45, %46, %47, %48, %49, %50, %51, %52, %53, %54, %55, %56, %57, %58, %59, %60, %61, %62, %63}, %64, %65, p, 1, 1, 0, 1;\n}\n"
    : "+f"(d[0]), "+f"(d[1]), "+f"(d[2]), "+f"(d[3]), "+f"(d[4]), "+f"(d[5]), "+f"(d[6]), "+f"(d[7]), "+f"(d[8]), "+f"(d[9]), "+f"(d[10]), "+f"(d[11]), "+f"(d[12]), "+f"(d[13]), "+f"(d[14]), "+f"(d[15]), "+f"(d[16]), "+f"(d[17]), "+f"(d[18]), "+f"(d[19]), "+f"(d[20]), "+f"(d[21]), "+f"(d[22]), "+f"(d[23]), "+f"(d[24]), "+f"(d[25]), "+f"(d[26]), "+f"(d[27]), "+f"(d[28]), "+f"(d[29]), "+f"(d[30]), "+f"(d[31]), "+f"(d[32]), "+f"(d[33]), "+f"(d[34]), "+f"(d[35]), "+f"(d[36]), "+f"(d[37]), "+f"(d[38]), "+f"(d[39]), "+f"(d[40]), "+f"(d[41]), "+f"(d[42]), "+f"(d[43]), "+f"(d[44]), "+f"(d[45]), "+f"(d[46]), "+f"(d[47]), "+f"(d[48]), "+f"(d[49]), "+f"(d[50]), "+f"(d[51]), "+f"(d[52]), "+f"(d[53]), "+f"(d[54]), "+f"(d[55]), "+f"(d[56]), "+f"(d[57]), "+f"(d[58]), "+f"(d[59]), "+f"(d[60]), "+f"(d[61]), "+f"(d[62]), "+f"(d[63])
    : "l"(da), "l"(db), "r"(scale_d));
}
__device__ __forceinline__ void wgmma_ss_n40_tt(float (&d)[20], uint64_t da, uint64_t db, int scale_d) {
  asm volatile("{\n.reg .pred p;\nsetp.ne.b32 p, %22, 0;\n"
    "wgmma.mma_async.sync.aligned.m64n40k16.f32.bf16.bf16 "
    "{%0, %1, %2, %3, %4, %5, %6, %7, %8, %9, %10, %11, %12, %13, %14, %15, %16, %17, %18, %19}, %20, %21, p, 1, 1, 1, 1;\n}\n"
    : "+f"(d[0]), "+f"(d[1]), "+f"(d[2]), "+f"(d[3]), "+f"(d[4]), "+f"(d[5]), "+f"(d[6]), "+f"(d[7]), "+f"(d[8]), "+f"(d[9]), "+f"(d[10]), "+f"(d[11]), "+f"(d[12]), "+f"(d[13]), "+f"(d[14]), "+f"(d[15]), "+f"(d[16]), "+f"(d[17]), "+f"(d[18]), "+f"(d[19])
    : "l"(da), "l"(db), "r"(scale_d));
}
__device__ __forceinline__ void wgmma_rs_n32(float (&d)[16], uint32_t a0, uint32_t a1, uint32_t a2, uint32_t a3, uint64_t db, int scale_d) {
  asm volatile("{\n.reg .pred p;\nsetp.ne.b32 p, %21, 0;\n"
    "wgmma.mma_async.sync.aligned.m64n32k16.f32.bf16.bf16 "
    "{%0, %1, %2, %3, %4, %5, %6, %7, %8, %9, %10, %11, %12, %13, %14, %15}, {%16, %17, %18, %19}, %20, p, 1, 1, 1;\n}\n"
    : "+f"(d[0]), "+f"(d[1]), "+f"(d[2]), "+f"(d[3]), "+f"(d[4]), "+f"(d[5]), "+f"(d[6]), "+f"(d[7]), "+f"(d[8]), "+f"(d[9]), "+f"(d[10]), "+f"(d[11]), "+f"(d[12]), "+f"(d[13]), "+f"(d[14]), "+f"(d[15])
    : "r"(a0), "r"(a1), "r"(a2), "r"(a3), "l"(db), "r"(scale_d));
}
__device__ __forceinline__ void wgmma_ss_n32_nt(float (&d)[16], uint64_t da, uint64_t db, int scale_d) {
  asm volatile("{\n.reg .pred p;\nsetp.ne.b32 p, %18, 0;\n"
    "wgmma.mma_async.sync.aligned.m64n32k16.f32.bf16.bf16 "
    "{%0, %1, %2, %3, %4, %5, %6, %7, %8, %9, %10, %11, %12, %13, %14, %15}, %16, %17, p, 1, 1, 0, 1;\n}\n"
    : "+f"(d[0]), "+f"(d[1]), "+f"(d[2]), "+f"(d[3]), "+f"(d[4]), "+f"(d[5]), "+f"(d[6]), "+f"(d[7]), "+f"(d[8]), "+f"(d[9]), "+f"(d[10]), "+f"(d[11]), "+f"(d[12]), "+f"(d[13]), "+f"(d[14]), "+f"(d[15])
    : "l"(da), "l"(db), "r"(scale_d));
}

template <int N>
struct MMA;
__device__ __forceinline__ uint64_t bdesc(uint32_t lo) { return ((uint64_t)0x40000040u << 32) | lo; }
template <>
struct MMA<256> {
  static __device__ __forceinline__ void run(float (&d)[128], uint64_t a, uint32_t b, int s, uint32_t gs) {
    wgmma_ss_n128(*reinterpret_cast<float(*)[64]>(&d[0]), a, bdesc(b), s);
    wgmma_ss_n128(*reinterpret_cast<float(*)[64]>(&d[64]), a, bdesc(b + 2 * gs), s);
  }
};
template <>
struct MMA<192> {
  static __device__ __forceinline__ void run(float (&d)[96], uint64_t a, uint32_t b, int s, uint32_t) { wgmma_ss_n192(d, a, bdesc(b), s); }
};
template <>
struct MMA<128> {
  static __device__ __forceinline__ void run(float (&d)[64], uint64_t a, uint32_t b, int s, uint32_t) { wgmma_ss_n128(d, a, bdesc(b), s); }
};

#define TSTAMP(idx)
#define TSTAMP_IF(c, idx)

__device__ __forceinline__ uint32_t offB2(int s) { return s * 16384 + (s >= 6 ? 49152 : 0); }
__device__ __forceinline__ uint32_t offA2(int s) { return 98304 + (s >> 1) * 16384 + (s >= 6 ? 32768 : 0); }
__device__ __forceinline__ uint32_t off4(int s) { return (s ^ ((s >> 1) & 1)) * 32768; }
template <int NS, int START, int COUNT, int STEP, class F>
__device__ __forceinline__ void ring_loop(F&& f) {
  int s = START;
#pragma unroll 1
  for (int i = 0; i < COUNT; i++) {
    f(s);
    s += STEP;
    if (s == NS) s = 0;
  }
}
struct LoopState { bool ready; };
template <int N, int KS, int NS, int START, int COUNT, bool CONT, bool CHAIN_IN = false, bool CHAIN_OUT = false, int PREV0 = 0>
__device__ __forceinline__ void mainloop(float (&acc)[N / 2], uint32_t& ph, uint32_t sb, int w, int t, int ebase, LoopState& ls) {
  constexpr uint32_t FULLB = KS == 2 ? B_FULL24 : B_FULL32, EMPTYB = KS == 2 ? B_EMPTY24 : B_EMPTY32;
  constexpr bool EARLY = (EARLYREL >> (KS == 4 ? 1 : 0)) & 1;
  uint32_t dA0 = (uint32_t)make_desc(1024 + SM_RING + w * 8192, 16, 1024, 1);
  constexpr uint32_t dB0 = ((1024 + SM_RING) >> 4) | ((KS * 2048 >> 4) << 16);
  auto desc = [](uint32_t lo) { return ((uint64_t)0x40000040u << 32) | lo; };
  const bool rel = (t & 95) == 0;
  uint32_t remote;
  asm("mapa.shared::cluster.u32 %0, %1, %2;" : "=r"(remote) : "r"(sb + EMPTYB), "r"((t >> 5) & 1));
  auto release = [&](int s) {
    if (rel) asm volatile("mbarrier.arrive.shared::cluster.b64 _, [%0];" ::"r"(remote + 8 * s) : "memory");
  };
  bool ready = CHAIN_IN ? ls.ready : mbar_test(sb + FULLB + 8 * START, ph);
  bool pending = CHAIN_IN;
  bool first = !CONT;
  int kbs = 0;
  auto step = [&](const int S, const bool first_of_call = false) {
    const int PREV = (CHAIN_IN && first_of_call) ? PREV0 : (S + NS - 1) % NS, NEXT = (S + 1) % NS;
    if (__builtin_expect(!ready, 0)) {
      if (pending) {
        wg_wait<0>();
        release(PREV);
        pending = false;
      }
      mbar_wait_nl(sb + FULLB + 8 * S, ph);
    }
    if (KBSTAMP) { TSTAMP_IF(t == 0 && w == 0, 64 + ebase + kbs); kbs++; }
    const uint32_t da = dA0 + ((KS == 2 ? offA2(S) + (S & 1) * 64 : off4(S)) >> 4);
    const uint32_t db = dB0 + ((KS == 2 ? offB2(S) : off4(S) + 16384) >> 4);
    wg_fence();
    if constexpr (EARLY) {
      MMA<N>::run(acc, desc(da), db, first ? 0 : 1, KS * 128);
      wg_commit();
      if (pending) {
        wg_wait<1>();
        release(PREV);
      }
#pragma unroll
      for (int k = 1; k < KS; k++) MMA<N>::run(acc, desc(da + k * 2), db + k * 128, 1, KS * 128);
      wg_commit();
      if (NEXT == 0) ph ^= 1;
      ready = mbar_test(sb + FULLB + 8 * NEXT, ph);
    } else {
#pragma unroll
      for (int k = 0; k < KS; k++) MMA<N>::run(acc, desc(da + k * 2), db + k * 128, (k == 0 && first) ? 0 : 1, KS * 128);
      wg_commit();
      if (NEXT == 0) ph ^= 1;
      ready = mbar_test(sb + FULLB + 8 * NEXT, ph);
      if (pending) {
        wg_wait<1>();
        release(PREV);
      }
    }
    pending = true;
    first = false;
  };
  constexpr int LEAD = START == 0 ? 0 : (NS - START < COUNT ? NS - START : COUNT);
  constexpr int ROUNDS = (COUNT - LEAD) / NS, TAIL = (COUNT - LEAD) % NS;
  static_assert(!CHAIN_IN || PREV0 == (START + NS - 1) % NS || START == 0, "bad chain");
  if constexpr (CHAIN_IN && PREV0 != (START + NS - 1) % NS) {
#pragma unroll
    for (int i = 0; i < NS; i++) step(i, i == 0);
  }
  constexpr int PEEL = (CHAIN_IN && PREV0 != (START + NS - 1) % NS) ? 1 : 0;
#pragma unroll
  for (int i = 0; i < LEAD; i++) step(START + i);
#pragma unroll 1
  for (int r = 0; r < ROUNDS - PEEL; r++) {
    dA0 = __shfl_sync(0xffffffffu, dA0, 0);
#pragma unroll
    for (int i = 0; i < NS; i++) step(i);
  }
#pragma unroll
  for (int i = 0; i < TAIL; i++) step(i);
  if constexpr (CHAIN_OUT) {
    ls.ready = ready;
  } else {
    wg_wait<0>();
    release((START + COUNT - 1) % NS);
    fence_regs(acc);
  }
}

__device__ __forceinline__ uint32_t bmax2(uint32_t a, uint32_t b) { uint32_t r; asm("max.bf16x2 %0, %1, %2;" : "=r"(r) : "r"(a), "r"(b)); return r; }
__device__ __forceinline__ uint32_t bmin2(uint32_t a, uint32_t b) { uint32_t r; asm("min.bf16x2 %0, %1, %2;" : "=r"(r) : "r"(a), "r"(b)); return r; }
__device__ __forceinline__ float4 lds128f(uint32_t a) {
  float4 v;
  asm volatile("ld.shared.v4.f32 {%0, %1, %2, %3}, [%4];" : "=f"(v.x), "=f"(v.y), "=f"(v.z), "=f"(v.w) : "r"(a));
  return v;
}
template <bool DEN>
__device__ __forceinline__ float hedgehog_row(const uint32_t (&w)[16], uint32_t (&out)[32], uint32_t zaddr) {
  constexpr float L2E = 1.4426950408889634f;
  uint32_t mx2[8], mn2[8];
#pragma unroll
  for (int i = 0; i < 8; i++) { mx2[i] = bmax2(w[2 * i], w[2 * i + 1]); mn2[i] = bmin2(w[2 * i], w[2 * i + 1]); }
#pragma unroll
  for (int st = 4; st > 0; st >>= 1)
#pragma unroll
    for (int i = 0; i < st; i++) { mx2[i] = bmax2(mx2[i], mx2[i + st]); mn2[i] = bmin2(mn2[i], mn2[i + st]); }
  const float a = -fmaxf(bf_lo(mx2[0]), bf_hi(mx2[0])) * L2E;
  const float b = fminf(bf_lo(mn2[0]), bf_hi(mn2[0])) * L2E;
  float den = 0.f;
#pragma unroll
  for (int sgn = 0; sgn < 2; sgn++) {
    const float mul = sgn ? -L2E : L2E, off = sgn ? b : a;
    float e[32];
#pragma unroll
    for (int i = 0; i < 16; i++) {
      e[2 * i] = ex2f(fmaf(bf_lo(w[i]), mul, off));
      e[2 * i + 1] = ex2f(fmaf(bf_hi(w[i]), mul, off));
    }
    float s0 = 0.f, s1 = 0.f, s2 = 0.f, s3 = 0.f;
#pragma unroll
    for (int i = 0; i < 8; i++) { s0 += e[4 * i]; s1 += e[4 * i + 1]; s2 += e[4 * i + 2]; s3 += e[4 * i + 3]; }
    const float r = rcpf((s0 + s1) + (s2 + s3));
    if (DEN) {
      float d0 = 0.f, d1 = 0.f, d2 = 0.f, d3 = 0.f;
#pragma unroll
      for (int i = 0; i < 8; i++) {
        const float4 z = lds128f(zaddr + sgn * 128 + i * 16);
        d0 = fmaf(e[4 * i], z.x, d0); d1 = fmaf(e[4 * i + 1], z.y, d1);
        d2 = fmaf(e[4 * i + 2], z.z, d2); d3 = fmaf(e[4 * i + 3], z.w, d3);
      }
      den = fmaf((d0 + d1) + (d2 + d3), r, den);
    }
#pragma unroll
    for (int i = 0; i < 16; i++) out[16 * sgn + i] = pack_bf16(e[2 * i] * r, e[2 * i + 1] * r);
  }
  return den;
}
__device__ __forceinline__ uint4 lds128(uint32_t a) {
  uint4 v;
  asm volatile("ld.shared.v4.u32 {%0, %1, %2, %3}, [%4];" : "=r"(v.x), "=r"(v.y), "=r"(v.z), "=r"(v.w) : "r"(a) : "memory");
  return v;
}
__device__ __forceinline__ void sts128(uint32_t a, uint32_t x, uint32_t y, uint32_t z, uint32_t w) {
  asm volatile("st.shared.v4.u32 [%0], {%1, %2, %3, %4};" ::"r"(a), "r"(x), "r"(y), "r"(z), "r"(w) : "memory");
}

__device__ __forceinline__ float gelu2(float v) {
  constexpr float C0 = 0.7978845608028654f, C1 = 0.7978845608028654f * 0.044715f;
  const float u = v * fmaf(v * v, C1, C0);
  return fmaf(v, tanhf_hw(u), v);
}
__device__ __forceinline__ uint32_t badd2(uint32_t a, uint32_t b) { uint32_t r; asm("add.rn.bf16x2 %0, %1, %2;" : "=r"(r) : "r"(a), "r"(b)); return r; }
__device__ __forceinline__ uint4 gelu8(uint4 x, uint4 b) {
  const uint32_t v0 = badd2(x.x, b.x), v1 = badd2(x.y, b.y), v2 = badd2(x.z, b.z), v3 = badd2(x.w, b.w);
  uint4 r;
  r.x = pack_bf16(gelu2(bf_lo(v0)), gelu2(bf_hi(v0)));
  r.y = pack_bf16(gelu2(bf_lo(v1)), gelu2(bf_hi(v1)));
  r.z = pack_bf16(gelu2(bf_lo(v2)), gelu2(bf_hi(v2)));
  r.w = pack_bf16(gelu2(bf_lo(v3)), gelu2(bf_hi(v3)));
  return r;
}
__device__ __forceinline__ float warp_sum(float v) {
#pragma unroll
  for (int o = 16; o > 0; o >>= 1) v += __shfl_xor_sync(0xffffffffu, v, o);
  return v;
}
#define CTA_CONTEXT()                                                                        \
  uint32_t cta_u, rank_u;                                                                    \
  asm volatile("mov.u32 %0, %%ctaid.x;" : "=r"(cta_u));                                      \
  asm volatile("mov.u32 %0, %%cluster_ctarank;" : "=r"(rank_u));                             \
  const int cta = (int)cta_u, rank = (int)rank_u, cl = cta >> 1;                             \
  const uint32_t sb = (rank_u << 24) + 1024u;      \
  const int m = CL2M(cl), nn = CL2P(cl) * 2 + rank, row0 = m * 128;                          \
  (void)cta; (void)nn; (void)row0; (void)sb;
#define CL2M(cl) (((cl) >> 4) * 4 + (((cl) >> 1) & 3))
#define CL2P(cl) ((((cl) >> 3) & 1) * 2 + ((cl) & 1))

__global__ void __cluster_dims__(2, 1, 1) __launch_bounds__(512, 1) fused_kernel(const __grid_constant__ Params P) {
  extern __shared__ __align__(1024) uint8_t smem_raw[];
  const int tid = threadIdx.x;
  const int wg = __shfl_sync(0xffffffffu, tid >> 7, 0);
  const int t = tid & 127;
  {
  CTA_CONTEXT();
  if (tid < 32) {
    if (elect_one()) {
      prefetch_tmap(&P.xa);
      prefetch_tmap(&P.wqkv32);
      if (sb != smem_u32(smem_raw)) __trap();
#pragma unroll
      for (int s = 0; s < 8; s++) mbar_init(sb + B_FULL24 + 8 * s, 1);
      asm volatile("fence.mbarrier_init.release.cluster;" ::: "memory");
      fence_async_smem();
      TSTAMP(0);
#pragma unroll
      for (int i = 0; i < 2; i++) {
        const uint32_t fb = sb + B_FULL24 + 8 * i, bb = sb + SM_RING + offB2(i);
        mbar_expect_tx(fb, (i & 1) ? 16384 : 32768);
        if (!(i & 1)) {
          tma_2d(sb + SM_RING + offA2(i), &P.xa, fb, i * 32, row0, L2_NORMAL);
          tma_2d(sb + SM_RING + offA2(i) + 8192, &P.xa, fb, i * 32, row0 + 64, L2_NORMAL);
        }
        tma_3d(bb, &P.wqkv32, fb, 0, i * 32, 16 + 2 * nn, POL_W);
        tma_3d(bb + 8192, &P.wqkv32, fb, 0, i * 32, 32 + 2 * nn, POL_W);
      }
      TSTAMP(44);
    }
    __syncwarp();
  } else if (tid == 32) {
    for (int s = 0; s < 8; s++) mbar_init(sb + B_EMPTY24 + 8 * s, 4);
    for (int s = 0; s < NS32; s++) { mbar_init(sb + B_FULL32 + 8 * s, 1); mbar_init(sb + B_EMPTY32 + 8 * s, 4); }
    for (int s = 0; s < 4; s++) mbar_init(sb + B_DUMP + 8 * s, 256);
    mbar_init(sb + B_SFREE, 128);
    mbar_init(sb + B_GATES, 128);
    mbar_init(sb + B_SLO, 2);
    mbar_init(sb + B_WPHI, 1);
    for (int s = 0; s < 5; s++) mbar_init(sb + B_FLAG + 8 * s, 1);
    asm volatile("fence.mbarrier_init.release.cluster;" ::: "memory");
  }
  }
  __syncthreads();
  asm volatile("barrier.cluster.arrive.relaxed.aligned;" ::: "memory");

  if (wg == 0) {
    asm volatile("setmaxnreg.dec.sync.aligned.u32 40;");
    CTA_CONTEXT();
    if (tid < 32 && elect_one()) {
#pragma unroll
      for (int i = 2; i < 8; i++) {
        const uint32_t fb = sb + B_FULL24 + 8 * i, bb = sb + SM_RING + offB2(i);
        mbar_expect_tx(fb, (i & 1) ? 16384 : 32768);
        if (!(i & 1)) {
          tma_2d(sb + SM_RING + offA2(i), &P.xa, fb, i * 32, row0, L2_NORMAL);
          tma_2d(sb + SM_RING + offA2(i) + 8192, &P.xa, fb, i * 32, row0 + 64, L2_NORMAL);
        }
        tma_3d(bb, &P.wqkv32, fb, 0, i * 32, 16 + 2 * nn, POL_W);
        tma_3d(bb + 8192, &P.wqkv32, fb, 0, i * 32, 32 + 2 * nn, POL_W);
      }
    }
    __syncwarp();
    asm volatile("barrier.cluster.wait.acquire.aligned;" ::: "memory");
    if ((tid >> 5) == (PWARP ^ 1) && elect_one()) {
      const uint32_t ep = load_epoch();
      wait_flag(g_cnt + (C_Y + m) * 32, ep * 8);
      mbar_arrive(sb + B_FLAG + 0);
      wait_flag(g_cnt + (C_SYNC + 16 + nn) * 32, ep * 16);
      mbar_arrive(sb + B_FLAG + 32);
      wait_flag(g_cnt + (C_H1 + m) * 32, ep * 8);
      wait_flag(g_cnt + (C_SYNC + nn) * 32, ep * 16);
      mbar_arrive(sb + B_FLAG + 8);
      wait_flag(g_cnt + (C_H2 + m) * 32, ep * 8);
      mbar_arrive(sb + B_FLAG + 16);
      wait_flag(g_cnt + (C_O + m) * 32, ep * 8);
      mbar_arrive(sb + B_FLAG + 24);
    }
    if ((tid >> 5) == PWARP && elect_one()) {
      prefetch_tmap(&P.y); prefetch_tmap(&P.wqkv); prefetch_tmap(&P.w1a); prefetch_tmap(&P.w1b); prefetch_tmap(&P.h);
      prefetch_tmap(&P.w2); prefetch_tmap(&P.o); prefetch_tmap(&P.wo);
      const int rowh = row0 + rank * 64;
      uint32_t ph24 = 0;
      {
        constexpr uint32_t F2E = B_FULL24 - B_EMPTY24;
        int k = 0;
        auto pair = [&](const int tile, const int NS, const int S) {
          const uint32_t eb = sb + B_EMPTY24 + 8 * S, fb = eb + F2E;
          const uint32_t bb = sb + SM_RING + offB2(S), ab = sb + SM_RING + offA2(S) + rank * 8192;
          const uint32_t bbytes = tile == 2 ? 12288 : 16384;
          PWAIT(eb, ph24);
          mbar_expect_tx(fb, (NOA ? 0 : 16384) + bbytes);
          if (tile == 0) {
            tma_3d(bb, &P.wqkv32, fb, 0, k, 16 + 2 * nn, POL_W);
            tma_3d(bb + 8192, &P.wqkv32, fb, 0, k, 32 + 2 * nn, POL_W);
          } else if (tile == 1) tma_3d(bb, &P.w1a, fb, 0, k, 7 * nn, POL_W);
          else tma_3d(bb, &P.w1b, fb, 0, k, 7 * nn + 4, POL_W);
          PWAIT(eb + 8, ph24);
          if (!NOA) tma_2d_mc(ab, tile == 0 ? &P.xa : &P.y, fb, k, rowh, L2_NORMAL);
          mbar_expect_tx(fb + 8, bbytes);
          if (tile == 0) {
            tma_3d(bb + 16384, &P.wqkv32, fb + 8, 0, k + 32, 16 + 2 * nn, POL_W);
            tma_3d(bb + 16384 + 8192, &P.wqkv32, fb + 8, 0, k + 32, 32 + 2 * nn, POL_W);
          } else if (tile == 1) tma_3d(bb + 16384, &P.w1a, fb + 8, 0, k + 32, 7 * nn, POL_W);
          else tma_3d(bb + 16384, &P.w1b, fb + 8, 0, k + 32, 7 * nn + 4, POL_W);
          k += 64;
          if (S + 2 == NS) ph24 ^= 1;
        };
        k = 4 * 64;
        ring_loop<8, 0, 8, 2>([&](const int S) { pair(0, 8, S); });
        ring_loop<6, 0, 4, 2>([&](const int S) { pair(0, 6, S); });
        mbar_wait(sb + B_FLAG + 0, 0);
        fence_async_all();
        TSTAMP(40);
        k = 0;
        ring_loop<6, 2, 16, 2>([&](const int S) { pair(1, 6, S); });
        k = 0;
        ring_loop<6, 4, 16, 2>([&](const int S) { pair(2, 6, S); });
      }
      uint32_t ph = 1;
      int col = 0;
      auto entry = [&](const int S, const CUtensorMap* ma, const CUtensorMap* mb, int bgroup) {
        const uint32_t fb = sb + B_FULL32 + 8 * S, sa = sb + SM_RING + off4(S);
        mbar_expect_tx(fb, 32768);
        tma_2d_mc(sa + rank * 8192, ma, fb, col, rowh, POL_W);
        tma_3d(sa + 16384, mb, fb, 0, col, bgroup, POL_W);
        if (S == NS32 - 1) ph ^= 1;
      };
      asm volatile("red.relaxed.gpu.global.add.u32 [%0], 1;" ::"l"(g_cnt + (C_SYNC + 16 + nn) * 32) : "memory");
      mbar_wait(sb + B_FLAG + 32, 0);
#pragma unroll
      for (int j = 0; j < NS32; j++) {
        if (j == 0) mbar_wait(sb + B_EMPTY24 + 8 * 1, ph24);
        else if (j == 1) mbar_wait(sb + B_EMPTY24 + 8 * 3, ph24);
        else if (j == 3) mbar_wait(sb + B_EMPTY24 + 8 * 5, ph24);
        else if (j == 4) mbar_wait(sb + B_SLO, 0);
        entry(j, &P.xa, &P.wqkv, 2 * nn);
        col += 64;
      }
      ring_loop<NS32, 0, 11, 1>([&](const int S) {
        PWAIT(sb + B_EMPTY32 + 8 * S, ph);
        entry(S, &P.xa, &P.wqkv, 2 * nn);
        col += 64;
      });
      asm volatile("red.relaxed.gpu.global.add.u32 [%0], 1;" ::"l"(g_cnt + (C_SYNC + nn) * 32) : "memory");
      mbar_wait(sb + B_FLAG + 8, 0);
      fence_async_all();
      TSTAMP(41);
      const int rot = ROT_F;
      col = 448 * (rot & 7);
      int sub = 0;
      ring_loop<NS32, 1, 32, 1>([&](const int S) {
        PWAIT(sb + B_EMPTY32 + 8 * S, ph);
        entry(S, &P.h, &P.w2, 2 * nn);
        col += 64;
        if (++sub == 4) { sub = 0; col += 192; if (col == F_) col = 0; }
      });
      mbar_wait(sb + B_FLAG + 16, 0);
      fence_async_all();
      TSTAMP(42);
      col = 256 + 448 * (rot & 7);
      ring_loop<NS32, 3, 24, 1>([&](const int S) {
        PWAIT(sb + B_EMPTY32 + 8 * S, ph);
        entry(S, &P.h, &P.w2, 2 * nn);
        col += 64;
        if (++sub == 3) { sub = 0; col += 256; if (col > F_) col = 256; }
      });
      mbar_wait(sb + B_FLAG + 24, 0);
      fence_async_all();
      TSTAMP(43);
      col = 128 * (rot & 7);
      ring_loop<NS32, 2, 16, 1>([&](const int S) {
        PWAIT(sb + B_EMPTY32 + 8 * S, ph);
        entry(S, &P.o, &P.wo, 2 * nn);
        col = (col + 64) & (D_ - 1);
      });
      ring_loop<NS32, 3, NS32, 1>([&](const int S) {
        PWAIT(sb + B_EMPTY32 + 8 * S, ph);
        if (S == NS32 - 1) ph ^= 1;
      });
    }
  } else if (wg <= 2) {
    TSTAMP_IF(tid == 128, 47);
    asm volatile("setmaxnreg.inc.sync.aligned.u32 168;");
    CTA_CONTEXT();
    TSTAMP_IF(tid == 128, 48);
    asm volatile("barrier.cluster.wait.acquire.aligned;" ::: "memory");
    TSTAMP_IF(tid == 128, 49);
    const int w = wg - 1;
    const int warp = t >> 5, lane = t & 31, q = lane & 3;
    const int rloc = w * 64 + warp * 16 + (lane >> 2);
    const int srow = w * 64 + warp * 16 + ((lane >> 3) & 1) * 8 + (lane & 7);
    const uint32_t st_row = srow * 128, st_x = srow & 7, st_hi = lane >> 4;
    LoopState ls;
    {
      uint32_t ph = 0;
      {
        float acc[128];
        mainloop<256, 2, 8, 0, 24, false, false, true>(acc, ph, sb, w, t, 0, ls);
        mainloop<256, 2, 6, 0, 8, true, true, false, 7>(acc, ph, sb, w, t, 200, ls);
        BST(3);
        TSTAMP_IF(t == 0, 1 + w);
        {
          uint32_t kp[32], vp[32];
#pragma unroll
          for (int i = 0; i < 32; i++) {
            vp[i] = pack_bf16(acc[64 + 2 * i], acc[64 + 2 * i + 1]);
            asm volatile("" : "+r"(vp[i]));
          }
#pragma unroll
          for (int i = 0; i < 32; i++) kp[i] = pack_bf16(acc[2 * i], acc[2 * i + 1]);
          TSTAMP_IF(t == 0 && w == 0, 430);
          mbar_wait_nl(sb + B_WPHI, 0);
          TSTAMP_IF(t == 0 && w == 0, 431);
          const uint64_t dW = make_desc(sb + SM_X, 16, 512, 2);
          float p[4][16];
          wg_fence();
#pragma unroll
          for (int h = 0; h < 4; h++) wgmma_rs_n32(p[h], kp[8 * h], kp[8 * h + 1], kp[8 * h + 2], kp[8 * h + 3], dW + h * 128, 0);
#pragma unroll
          for (int h = 0; h < 4; h++) wgmma_rs_n32(p[h], kp[8 * h + 4], kp[8 * h + 5], kp[8 * h + 6], kp[8 * h + 7], dW + h * 128 + 64, 1);
          wg_commit();
          BST(6);
          TSTAMP_IF(t == 0 && w == 0, 432);
#pragma unroll
          for (int h = 0; h < 4; h++) {
            const uint32_t tb = sb + SM_STG + h * 16384 + st_row;
            stsm_x4(tb + (((0 + st_hi) ^ st_x) << 4), vp[8 * h], vp[8 * h + 1], vp[8 * h + 2], vp[8 * h + 3]);
            stsm_x4(tb + (((2 + st_hi) ^ st_x) << 4), vp[8 * h + 4], vp[8 * h + 5], vp[8 * h + 6], vp[8 * h + 7]);
          }
          TSTAMP_IF(t == 0 && w == 0, 433);
          wg_wait<0>();
          BST(7);
          TSTAMP_IF(t == 0 && w == 0, 434);
#pragma unroll
          for (int h = 0; h < 4; h++) {
            fence_regs(p[h]);
            const uint32_t tb = sb + SM_STG + h * 16384 + st_row;
            stsm_x4(tb + (((4 + st_hi) ^ st_x) << 4), pack_bf16(p[h][0], p[h][1]), pack_bf16(p[h][2], p[h][3]),
                    pack_bf16(p[h][4], p[h][5]), pack_bf16(p[h][6], p[h][7]));
            stsm_x4(tb + (((6 + st_hi) ^ st_x) << 4), pack_bf16(p[h][8], p[h][9]), pack_bf16(p[h][10], p[h][11]),
                    pack_bf16(p[h][12], p[h][13]), pack_bf16(p[h][14], p[h][15]));
          }
          TSTAMP_IF(t == 0 && w == 0, 435);
          BST(4);
          fence_async_smem();
          mbar_arrive(sb + B_DUMP + 0);
          BST(5);
        }
        TSTAMP_IF(t == 0, 3 + w);
      }
      {
        float acc[128];
        mainloop<256, 2, 6, 2, 32, false>(acc, ph, sb, w, t, 201, ls);
        BST(0);
        TSTAMP_IF(t == 0, 5 + w);
        mbar_wait_nl(sb + B_SFREE, 0);
        BST(1);
#pragma unroll
        for (int i = 0; i < 16; i++)
          stsm_x4(sb + SM_STG + (i >> 2) * 16384 + st_row + (((2 * (i & 3) + st_hi) ^ st_x) << 4),
                  pack_bf16(acc[8 * i], acc[8 * i + 1]), pack_bf16(acc[8 * i + 2], acc[8 * i + 3]),
                  pack_bf16(acc[8 * i + 4], acc[8 * i + 5]), pack_bf16(acc[8 * i + 6], acc[8 * i + 7]));
        mbar_arrive(sb + B_DUMP + 8);
        BST(2);
        TSTAMP_IF(t == 0, 7 + w);
      }
      {
        float acc[96];
        mainloop<192, 2, 6, 4, 32, false>(acc, ph, sb, w, t, 202, ls);
        TSTAMP_IF(t == 0, 9 + w);
        mbar_wait_nl(sb + B_SFREE, 1);
#pragma unroll
        for (int i = 0; i < 12; i++)
          stsm_x4(sb + SM_STGH + (i >> 2) * 16384 + st_row + (((2 * (i & 3) + st_hi) ^ st_x) << 4),
                  pack_bf16(acc[8 * i], acc[8 * i + 1]), pack_bf16(acc[8 * i + 2], acc[8 * i + 3]),
                  pack_bf16(acc[8 * i + 4], acc[8 * i + 5]), pack_bf16(acc[8 * i + 6], acc[8 * i + 7]));
        mbar_arrive(sb + B_DUMP + 16);
        TSTAMP_IF(t == 0, 11 + w);
      }
    }
    {
      uint32_t ph = 0;
      uint32_t pq[32];
      {
        float acc[64];
        mainloop<128, 4, 5, 0, 16, false>(acc, ph, sb, w, t, 48, ls);
        TSTAMP_IF(t == 0, 13 + w);
        uint32_t qp[32];
#pragma unroll
        for (int i = 0; i < 32; i++) qp[i] = pack_bf16(acc[2 * i], acc[2 * i + 1]);
        mbar_wait_nl(sb + B_WPHI, 1);
        const uint64_t dW = make_desc(sb + SM_X, 16, 512, 2);
        float p[4][16];
        wg_fence();
#pragma unroll
        for (int h = 0; h < 4; h++) wgmma_rs_n32(p[h], qp[8 * h], qp[8 * h + 1], qp[8 * h + 2], qp[8 * h + 3], dW + h * 128, 0);
#pragma unroll
        for (int h = 0; h < 4; h++) wgmma_rs_n32(p[h], qp[8 * h + 4], qp[8 * h + 5], qp[8 * h + 6], qp[8 * h + 7], dW + h * 128 + 64, 1);
        wg_commit();
        wg_wait<0>();
#pragma unroll
        for (int h = 0; h < 4; h++) {
          fence_regs(p[h]);
#pragma unroll
          for (int i = 0; i < 8; i++) pq[8 * h + i] = pack_bf16(p[h][2 * i], p[h][2 * i + 1]);
        }
      }
      TSTAMP_IF(t == 0, 15 + w);
      float acc[64];
      mainloop<128, 4, 5, 1, 8, false, false, true>(acc, ph, sb, w, t, 64, ls);
      mbar_wait_nl(sb + B_SFREE, 0);
#pragma unroll
      for (int h = 0; h < 4; h++) {
        const uint32_t tb = sb + SM_STGH + (h >> 1) * 16384 + st_row;
        stsm_x4(tb + ((((h & 1) * 4 + 0 + st_hi) ^ st_x) << 4), pq[8 * h], pq[8 * h + 1], pq[8 * h + 2], pq[8 * h + 3]);
        stsm_x4(tb + ((((h & 1) * 4 + 2 + st_hi) ^ st_x) << 4), pq[8 * h + 4], pq[8 * h + 5], pq[8 * h + 6], pq[8 * h + 7]);
      }
      mbar_arrive(sb + B_DUMP + 24);
      mainloop<128, 4, 5, 4, 48, true, true, true, 3>(acc, ph, sb, w, t, 72, ls);
      float acc2[64];
      mbar_wait_nl(sb + B_GATES, 0);
      const float s0 = 1.f - lds_f32(sb + SM_GATE + 4 * rloc), s1 = 1.f - lds_f32(sb + SM_GATE + 4 * (rloc + 8));
#pragma unroll
      for (int j = 0; j < 16; j++) {
        const uint32_t bb = __float_as_uint(lds_f32(sb + SM_B2 + 2 * (8 * j + 2 * q)));
        acc2[4 * j] = s0 * bf_lo(bb); acc2[4 * j + 1] = s0 * bf_hi(bb);
        acc2[4 * j + 2] = s1 * bf_lo(bb); acc2[4 * j + 3] = s1 * bf_hi(bb);
      }
      mainloop<128, 4, 5, 2, 16, true, true, false, 1>(acc2, ph, sb, w, t, 120, ls);
      fence_regs(acc);
      TSTAMP_IF(t == 0, 17 + w);
      const float h0 = 0.5f * s0, h1 = 0.5f * s1;
      const uint32_t stg = sb + SM_RING + w * 8192 + (st_row - w * 8192);
#pragma unroll
      for (int i = 0; i < 8; i++) {
        const float* a1 = acc + 8 * i;
        const float* a2 = acc2 + 8 * i;
        const uint32_t r0 = pack_bf16(fmaf(a1[0], h0, a2[0]), fmaf(a1[1], h0, a2[1]));
        const uint32_t r1 = pack_bf16(fmaf(a1[2], h1, a2[2]), fmaf(a1[3], h1, a2[3]));
        const uint32_t r2 = pack_bf16(fmaf(a1[4], h0, a2[4]), fmaf(a1[5], h0, a2[5]));
        const uint32_t r3 = pack_bf16(fmaf(a1[6], h1, a2[6]), fmaf(a1[7], h1, a2[7]));
        stsm_x4(stg + (i >> 2) * 32768 + (((2 * (i & 3) + st_hi) ^ st_x) << 4), r0, r1, r2, r3);
      }
      fence_async_smem();
      if (w == 0) asm volatile("bar.sync 2, 128;" ::: "memory");
      else asm volatile("bar.sync 3, 128;" ::: "memory");
      if (t == 0) {
        tma_store_2d(&P.out, sb + SM_RING + w * 8192, 128 * nn, m * 128 + w * 64);
        tma_store_2d(&P.out, sb + SM_RING + w * 8192 + 32768, 128 * nn + 64, m * 128 + w * 64);
        asm volatile("cp.async.bulk.commit_group;" ::: "memory");
        asm volatile("cp.async.bulk.wait_group.read 0;" ::: "memory");
        TSTAMP(19 + w);
      }
    }
  } else {
    asm volatile("setmaxnreg.inc.sync.aligned.u32 136;");
    CTA_CONTEXT();
    const int warp = t >> 5, lane = t & 31, q = lane & 3;
    TSTAMP_IF(t == 0, 45);
    uint32_t ep = 0;
    if (t == 0) {
      mbar_expect_tx(sb + B_WPHI, 8192);
      tma_2d(sb + SM_X, &P.wphi, sb + B_WPHI, 0, nn * 128, L2_NORMAL);
      ep = load_epoch();
    }
    {
      const int r0 = m * 128 + nn * 16 + warp * 4;
      uint4 gw[4], xb[4][4];
#pragma unroll
      for (int u = 0; u < 4; u++)
#pragma unroll
        for (int i = 0; i < 4; i++)
          xb[u][i] = __ldg(reinterpret_cast<const uint4*>(P.A_x + (size_t)(r0 + u) * D_) + lane + 32 * i);
#pragma unroll
      for (int i = 0; i < 4; i++) gw[i] = __ldg(reinterpret_cast<const uint4*>(P.gate_w) + lane + 32 * i);
      {
        uint4* z = reinterpret_cast<uint4*>(g_kv + (size_t)nn * 4 * 64 * KVP) + m * 160;
        z[t] = make_uint4(0, 0, 0, 0);
        if (t < 32) z[128 + t] = make_uint4(0, 0, 0, 0);
      }
#pragma unroll
      for (int u = 0; u < 4; u++) {
        float sum = 0.f, dot = 0.f;
#pragma unroll
        for (int i = 0; i < 4; i++) {
          const uint32_t b[4] = {xb[u][i].x, xb[u][i].y, xb[u][i].z, xb[u][i].w};
          const uint32_t g[4] = {gw[i].x, gw[i].y, gw[i].z, gw[i].w};
#pragma unroll
          for (int k = 0; k < 4; k++) {
            sum += bf_lo(b[k]) + bf_hi(b[k]);
            dot = fmaf(bf_lo(b[k]), bf_lo(g[k]), dot);
            dot = fmaf(bf_hi(b[k]), bf_hi(g[k]), dot);
          }
        }
        const float mean = warp_sum(sum) * (1.f / D_);
        dot = warp_sum(dot);
        float var = 0.f;
#pragma unroll
        for (int i = 0; i < 4; i++) {
          const uint32_t b[4] = {xb[u][i].x, xb[u][i].y, xb[u][i].z, xb[u][i].w};
#pragma unroll
          for (int k = 0; k < 4; k++) {
            const float d0 = bf_lo(b[k]) - mean, d1 = bf_hi(b[k]) - mean;
            var = fmaf(d0, d0, var);
            var = fmaf(d1, d1, var);
          }
        }
        var = warp_sum(var) * (1.f / D_);
        const float rstd = rsqrtf(var + 1e-5f);
        uint4* dsty = reinterpret_cast<uint4*>(P.py + (size_t)(r0 + u) * D_) + lane;
#pragma unroll
        for (int i = 0; i < 4; i++) {
          const uint32_t b[4] = {xb[u][i].x, xb[u][i].y, xb[u][i].z, xb[u][i].w};
          uint32_t o[4];
#pragma unroll
          for (int k = 0; k < 4; k++) o[k] = pack_bf16((bf_lo(b[k]) - mean) * rstd, (bf_hi(b[k]) - mean) * rstd);
          dsty[32 * i] = make_uint4(o[0], o[1], o[2], o[3]);
        }
        if (lane == 0) g_gate[r0 + u] = 1.f / (1.f + __expf(-dot));
      }
      TSTAMP_IF(t == 0, 46);
      fence_async_all();
      epi_bar();
      if (t == 0) {
        signal_flag(g_cnt + (C_Y + m) * 32);
        signal_flag(g_cnt + (C_ZERO + nn) * 32);
        TSTAMP(21);
      }
    }
    asm volatile("barrier.cluster.wait.acquire.aligned;" ::: "memory");
    {
      for (int p = t; p < 224; p += 128) sts_f32(sb + SM_B1 + 4 * p, __uint_as_float(reinterpret_cast<const uint32_t*>(P.b1)[224 * nn + p]));
      if (t < 64) sts_f32(sb + SM_B2 + 4 * t, __uint_as_float(reinterpret_cast<const uint32_t*>(P.b2)[64 * nn + t]));
      if (t == 0) {
        wait_flag(g_cnt + (C_Y + m) * 32, ep * 8);
        wait_flag(g_cnt + (C_ZERO + nn) * 32, ep * 16);
      }
      epi_bar();
      sts_f32(sb + SM_GATE + 4 * t, __ldcg(g_gate + m * 128 + t));
      mbar_arrive(sb + B_GATES);
      epi_bar();
    }
    const uint32_t my_row = t * 128, my_x = t & 7;
    {
      EWAIT(sb + B_DUMP + 0, 0);
      TSTAMP_IF(t == 0, 22);
      const uint64_t dPhi = make_desc(sb + SM_X, 1024, 1024, 1);
      float kv[20];
#pragma unroll
      for (int i = 0; i < 20; i++) kv[i] = 0.f;
      float* dst = g_kv + ((size_t)(nn * 4) * 64 + warp * 16 + (lane >> 2)) * KVP;
#pragma unroll 1
      for (int h = 0; h < (NOEPI ? 0 : 4); h++) {
        const uint32_t tb = sb + SM_STG + h * 16384 + my_row;
        uint32_t pw[16];
#pragma unroll
        for (int c = 0; c < 4; c++) {
          const uint4 v = lds128(tb + (((4 + c) ^ my_x) << 4));
          pw[4 * c] = v.x; pw[4 * c + 1] = v.y; pw[4 * c + 2] = v.z; pw[4 * c + 3] = v.w;
        }
        sts128(tb + ((4 ^ my_x) << 4), 0x00003f80u, 0u, 0u, 0u);
        uint32_t phi[32];
        hedgehog_row<false>(pw, phi, 0);
        TSTAMP_IF(t == 0, 400 + 4 * h);
        if (h > 0) {
          wg_wait<0>();
          fence_regs(kv);
#pragma unroll
          for (int j = 0; j < 4; j++) {
            asm volatile("red.global.add.v2.f32 [%0], {%1, %2};" ::"l"(dst + 8 * j + 2 * q), "f"(kv[4 * j]), "f"(kv[4 * j + 1]) : "memory");
            asm volatile("red.global.add.v2.f32 [%0], {%1, %2};" ::"l"(dst + 8 * KVP + 8 * j + 2 * q), "f"(kv[4 * j + 2]), "f"(kv[4 * j + 3]) : "memory");
          }
          if (q == 0) {
            asm volatile("red.global.add.f32 [%0], %1;" ::"l"(dst + 32), "f"(kv[16]) : "memory");
            asm volatile("red.global.add.f32 [%0], %1;" ::"l"(dst + 8 * KVP + 32), "f"(kv[18]) : "memory");
          }
          dst += 64 * KVP;
        }
        epi_bar();
        TSTAMP_IF(t == 0, 401 + 4 * h);
#pragma unroll
        for (int c = 0; c < 8; c++)
          sts128(sb + SM_X + my_row + ((c ^ my_x) << 4), phi[4 * c], phi[4 * c + 1], phi[4 * c + 2], phi[4 * c + 3]);
        fence_async_smem();
        epi_bar();
        TSTAMP_IF(t == 0, 402 + 4 * h);
        const uint64_t dV = make_desc(sb + SM_STG + h * 16384, 1024, 1024, 1);
        wg_fence();
#pragma unroll
        for (int k = 0; k < 8; k++) wgmma_ss_n40_tt(kv, dPhi + k * 128, dV + k * 128, k);
        wg_commit();
        TSTAMP_IF(t == 0, 403 + 4 * h);
      }
      wg_wait<0>();
      fence_regs(kv);
      mbar_arrive(sb + B_SFREE);
#pragma unroll
      for (int j = 0; j < 4; j++) {
        asm volatile("red.global.add.v2.f32 [%0], {%1, %2};" ::"l"(dst + 8 * j + 2 * q), "f"(kv[4 * j]), "f"(kv[4 * j + 1]) : "memory");
        asm volatile("red.global.add.v2.f32 [%0], {%1, %2};" ::"l"(dst + 8 * KVP + 8 * j + 2 * q), "f"(kv[4 * j + 2]), "f"(kv[4 * j + 3]) : "memory");
      }
      if (q == 0) {
        asm volatile("red.global.add.f32 [%0], %1;" ::"l"(dst + 32), "f"(kv[16]) : "memory");
        asm volatile("red.global.add.f32 [%0], %1;" ::"l"(dst + 8 * KVP + 32), "f"(kv[18]) : "memory");
      }
      epi_bar();
      if (t == 0) {
        mbar_expect_tx(sb + B_WPHI, 8192);
        tma_2d(sb + SM_X, &P.wphi, sb + B_WPHI, 0, nn * 128, L2_NORMAL);
        signal_flag(g_cnt + (C_KV + nn) * 32);
        TSTAMP(23);
      }
    }
    {
      const uint4 b = lds128(sb + SM_B1 + 16 * lane);
      __nv_bfloat16* base = P.ph + (size_t)(m * 128 + warp * 32) * F_ + 448 * nn + 8 * lane;
      const uint32_t src = sb + SM_STG + (lane >> 3) * 16384 + warp * 32 * 128;
      EWAIT(sb + B_DUMP + 8, 0);
      TSTAMP_IF(t == 0, 24);
#pragma unroll 1
      for (int r = 0; r < (NOEPI ? 0 : 32); r += GR) {
        uint4 x[GR];
#pragma unroll
        for (int u = 0; u < GR; u++) x[u] = lds128(src + (r + u) * 128 + (((lane & 7) ^ ((r + u) & 7)) << 4));
#pragma unroll
        for (int u = 0; u < GR; u++) STH(reinterpret_cast<uint4*>(base + (size_t)(r + u) * F_), gelu8(x[u], b));
      }
      mbar_arrive(sb + B_SFREE);
      fence_async_all();
      epi_bar();
      if (t < 2) mbar_arrive_cluster(sb + B_SLO, t);
      if (t == 0) { signal_flag(g_cnt + (C_H1 + m) * 32); TSTAMP(25); }
    }
    {
      uint4 b[3];
      int ro[3], co[3];
#pragma unroll
      for (int u = 0; u < 3; u++) {
        const int L = u * 32 + lane;
        ro[u] = L / 24;
        co[u] = L % 24;
        b[u] = lds128(sb + SM_B1 + 512 + 16 * co[u]);
      }
      __nv_bfloat16* base = P.ph + (size_t)(m * 128 + warp * 32) * F_ + 448 * nn + 256;
      EWAIT(sb + B_DUMP + 16, 0);
      TSTAMP_IF(t == 0, 26);
#pragma unroll 1
      for (int r = 0; r < (NOEPI ? 0 : 32); r += 4) {
        uint4 x[3];
#pragma unroll
        for (int u = 0; u < 3; u++) {
          const int row = warp * 32 + r + ro[u];
          x[u] = lds128(sb + SM_STGH + (co[u] >> 3) * 16384 + row * 128 + (((co[u] & 7) ^ (row & 7)) << 4));
        }
#pragma unroll
        for (int u = 0; u < 3; u++) STH(reinterpret_cast<uint4*>(base + (size_t)(r + ro[u]) * F_ + 8 * co[u]), gelu8(x[u], b[u]));
      }
      mbar_arrive(sb + B_SFREE);
      fence_async_all();
      epi_bar();
      if (t == 0) { signal_flag(g_cnt + (C_H2 + m) * 32); TSTAMP(27); }
    }
    {
      constexpr uint32_t SM_Z = SM_B1, SM_DEN = SM_B1 + 1024;
      if (t == 0) wait_flag(g_cnt + (C_KV + nn) * 32, ep * 16);
      epi_bar();
      {
        const float* ksrc = g_kv + (size_t)(nn * 4) * 64 * KVP;
        const float z0 = __ldcg(ksrc + t * KVP + 32), z1 = __ldcg(ksrc + (128 + t) * KVP + 32);
#pragma unroll
        for (int hp = 0; hp < 2; hp++) {
          float4 kvv[8];
#pragma unroll
          for (int u = 0; u < 8; u++) {
            const int idx = (hp * 8 + u) * 128 + t;
            kvv[u] = __ldcg(reinterpret_cast<const float4*>(ksrc + (idx >> 3) * KVP + 4 * (idx & 7)));
          }
#pragma unroll
          for (int u = 0; u < 8; u++) {
            const int idx = (hp * 8 + u) * 128 + t, f = idx >> 3, c4 = idx & 7;
            asm volatile("st.shared.v2.u32 [%0], {%1, %2};" ::"r"(sb + SM_KVZ + f * 64 + (((c4 >> 1) ^ ((f >> 1) & 3)) << 4) + (c4 & 1) * 8),
                         "r"(pack_bf16(kvv[u].x, kvv[u].y)), "r"(pack_bf16(kvv[u].z, kvv[u].w)) : "memory");
          }
        }
        sts_f32(sb + SM_Z + 4 * t, bf_lo(pack_bf16(z0, z0)));
        sts_f32(sb + SM_Z + 4 * (128 + t), bf_lo(pack_bf16(z1, z1)));
      }
      EWAIT(sb + B_DUMP + 24, 0);
      epi_bar();
      TSTAMP_IF(t == 0, 28);
#pragma unroll 1
      for (int h = 0; h < ((NOEPI || NOEPI3) ? 0 : 4); h++) {
        const uint32_t tb = sb + SM_STGH + (h >> 1) * 16384 + my_row;
        uint32_t pw[16];
#pragma unroll
        for (int c = 0; c < 4; c++) {
          const uint4 v = lds128(tb + ((((h & 1) * 4 + c) ^ my_x) << 4));
          pw[4 * c] = v.x; pw[4 * c + 1] = v.y; pw[4 * c + 2] = v.z; pw[4 * c + 3] = v.w;
        }
        TSTAMP_IF(t == 0 && h == 1, 420);
        uint32_t phi[32];
        const float den = hedgehog_row<true>(pw, phi, sb + SM_Z + h * 256);
        TSTAMP_IF(t == 0 && h == 1, 421);
        epi_bar();
        TSTAMP_IF(t == 0 && h == 1, 422);
#pragma unroll
        for (int c = 0; c < 8; c++)
          sts128(sb + SM_X + my_row + ((c ^ my_x) << 4), phi[4 * c], phi[4 * c + 1], phi[4 * c + 2], phi[4 * c + 3]);
        sts_f32(sb + SM_DEN + 4 * t, lds_f32(sb + SM_GATE + 4 * t) * rcpf(den + 1e-6f));
        TSTAMP_IF(t == 0 && h == 1, 423);
        fence_async_smem();
        epi_bar();
        TSTAMP_IF(t == 0 && h == 1, 424);
        const uint64_t dK = make_desc(sb + SM_KVZ + h * 4096, 16, 512, 2);
        const uint64_t dQ = make_desc(sb + SM_X, 16, 1024, 1);
        float nd[2][16];
        wg_fence();
#pragma unroll
        for (int k = 0; k < 4; k++)
#pragma unroll
          for (int hf = 0; hf < 2; hf++) wgmma_ss_n32_nt(nd[hf], dQ + hf * 512 + k * 2, dK + k * 64, k);
        wg_commit();
        TSTAMP_IF(t == 0 && h == 1, 425);
        wg_wait<0>();
        TSTAMP_IF(t == 0 && h == 1, 426);
#pragma unroll
        for (int hf = 0; hf < 2; hf++) {
          fence_regs(nd[hf]);
          const int rl = hf * 64 + warp * 16 + (lane >> 2);
          const float f0 = lds_f32(sb + SM_DEN + 4 * rl), f1 = lds_f32(sb + SM_DEN + 4 * (rl + 8));
          const int srow = hf * 64 + warp * 16 + ((lane >> 3) & 1) * 8 + (lane & 7);
          const uint32_t ob = sb + SM_STGH + (h >> 1) * 16384 + srow * 128;
#pragma unroll
          for (int c = 0; c < 2; c++)
            stsm_x4(ob + ((((h & 1) * 4 + 2 * c + (lane >> 4)) ^ (srow & 7)) << 4),
                    pack_bf16(nd[hf][8 * c] * f0, nd[hf][8 * c + 1] * f0), pack_bf16(nd[hf][8 * c + 2] * f1, nd[hf][8 * c + 3] * f1),
                    pack_bf16(nd[hf][8 * c + 4] * f0, nd[hf][8 * c + 5] * f0), pack_bf16(nd[hf][8 * c + 6] * f1, nd[hf][8 * c + 7] * f1));
        }
        TSTAMP_IF(t == 0 && h == 1, 427);
        TSTAMP_IF(t == 0 && h == 0, 419);
      }
      fence_async_smem();
      epi_bar();
      if (t == 0) {
        if (!(QSKIP & 4)) {
#pragma unroll
          for (int i = 0; i < 4; i++)
            tma_store_2d(&P.o, sb + SM_STGH + (i >> 1) * 16384 + (i & 1) * 8192, 128 * nn + (i >> 1) * 64, m * 128 + (i & 1) * 64);
          asm volatile("cp.async.bulk.commit_group;" ::: "memory");
          asm volatile("cp.async.bulk.wait_group 0;" ::: "memory");
        }
        signal_flag(g_cnt + (C_O + m) * 32);
        TSTAMP(29);
        asm volatile("red.relaxed.gpu.global.add.u32 [%0], 1;" ::"l"(g_cnt + C_DONE * 32) : "memory");
      }
    }
  }
}

typedef CUresult (*EncFn)(CUtensorMap*, CUtensorMapDataType, cuuint32_t, void*, const cuuint64_t*, const cuuint64_t*,
                          const cuuint32_t*, const cuuint32_t*, CUtensorMapInterleave, CUtensorMapSwizzle,
                          CUtensorMapL2promotion, CUtensorMapFloatOOBfill);

void encode(EncFn enc, CUtensorMap* m, int rank, const void* p, const cuuint64_t* dims, const cuuint64_t* strides,
            const cuuint32_t* box, CUtensorMapSwizzle swz, CUtensorMapL2promotion promo = PROMO_W) {
  cuuint32_t e[5] = {1, 1, 1, 1, 1};
  enc(m, CU_TENSOR_MAP_DATA_TYPE_BFLOAT16, rank, const_cast<void*>(p), dims, strides, box, e, CU_TENSOR_MAP_INTERLEAVE_NONE, swz,
      promo, CU_TENSOR_MAP_FLOAT_OOB_FILL_NONE);
}
void map_rows(EncFn enc, CUtensorMap* m, const void* p, int rows, int cols, int boxrows = 64) {
  cuuint64_t d[2] = {(cuuint64_t)cols, (cuuint64_t)rows}, s[1] = {(cuuint64_t)cols * 2};
  cuuint32_t b[2] = {64, (cuuint32_t)boxrows};
  encode(enc, m, 2, p, d, s, b, CU_TENSOR_MAP_SWIZZLE_128B, PROMO_A);
}
void map_w(EncFn enc, CUtensorMap* m, const void* p, int K, int N, int groups, int boxk = 64) {
  cuuint64_t d[3] = {64, (cuuint64_t)K, (cuuint64_t)N / 64}, s[2] = {(cuuint64_t)N * 2, 128};
  cuuint32_t b[3] = {64, (cuuint32_t)boxk, (cuuint32_t)groups};
  encode(enc, m, 3, p, d, s, b, CU_TENSOR_MAP_SWIZZLE_128B);
}
}

extern "C" void kernel_launch(void* const* d_in, const int* in_sizes, int n_in, void* d_out, int out_size) {
  (void)in_sizes; (void)n_in; (void)out_size;
  static EncFn enc = nullptr;
  static void *p_y, *p_h, *p_o;
  if (!enc) {
    void* fn = nullptr;
    cudaDriverEntryPointQueryResult qr;
    cudaGetDriverEntryPoint("cuTensorMapEncodeTiled", &fn, cudaEnableDefault, &qr);
    enc = (EncFn)fn;
    cudaGetSymbolAddress(&p_y, g_y);
    cudaGetSymbolAddress(&p_h, g_h);
    cudaGetSymbolAddress(&p_o, g_o);
    cudaFuncSetAttribute(fused_kernel, cudaFuncAttributeMaxDynamicSharedMemorySize, SM_TOTAL);
  }
  Params P;
  P.py = (__nv_bfloat16*)p_y; P.ph = (__nv_bfloat16*)p_h; P.po = (__nv_bfloat16*)p_o;
  map_rows(enc, &P.xa, d_in[0], S_, D_);
  map_rows(enc, &P.y, p_y, S_, D_);
  map_rows(enc, &P.h, p_h, S_, F_);
  map_rows(enc, &P.o, p_o, S_, D_);
  map_rows(enc, &P.out, d_out, S_, D_);
  map_w(enc, &P.wqkv, d_in[1], D_, 3 * D_, 2);
  map_w(enc, &P.wqkv32, d_in[1], D_, 3 * D_, 2, 32);
  map_w(enc, &P.w1a, d_in[5], D_, F_, 4, 32);
  map_w(enc, &P.w1b, d_in[5], D_, F_, 3, 32);
  map_w(enc, &P.w2, d_in[7], F_, D_, 2);
  map_w(enc, &P.wo, d_in[3], D_, D_, 2);
  {
    cuuint64_t d[2] = {32, 1024}, s[1] = {64};
    cuuint32_t b[2] = {32, 128};
    encode(enc, &P.wphi, 2, d_in[2], d, s, b, CU_TENSOR_MAP_SWIZZLE_64B);
  }
  P.A_x = (const __nv_bfloat16*)d_in[0];
  P.b1 = (const __nv_bfloat16*)d_in[6];
  P.b2 = (const __nv_bfloat16*)d_in[8];
  P.gate_w = (const __nv_bfloat16*)d_in[9];
  fused_kernel<<<NCTA, 512, SM_TOTAL, cudaStreamPerThread>>>(P);
}
```

```cpp
#include <cuda_runtime.h>
#include <cuda_bf16.h>
#include <cuda.h>
#include <stdint.h>

namespace {

constexpr int S_ = 2048, D_ = 1024, F_ = 3584;
constexpr int NCTA = 128;
constexpr int KVP = 40;
constexpr int NS32 = 5;

constexpr int PY = D_, PH = F_, PO = D_;
__device__ __align__(1024) __nv_bfloat16 g_y[S_ * PY];
__device__ __align__(1024) __nv_bfloat16 g_h[S_ * PH];
__device__ __align__(1024) __nv_bfloat16 g_o[S_ * PO];
__device__ __align__(1024) float g_kv[32 * 64 * KVP];
__device__ __align__(1024) float g_gate[S_];
__device__ __align__(1024) uint32_t g_cnt[96 * 32];
constexpr int C_ZERO = 0, C_KV = 8, C_Y = 16, C_H1 = 32, C_H2 = 48, C_O = 64, C_DONE = 80, C_SYNC = 81;

constexpr uint32_t SM_RING = 0;
constexpr uint32_t SM_STG = 147456;
constexpr uint32_t SM_STGH = SM_STG + 16384;
constexpr uint32_t SM_KVZ = SM_STG + 49152;
constexpr uint32_t SM_X = 212992;
constexpr uint32_t SM_MISC = 229376;
constexpr uint32_t SM_TOTAL = 232448;
constexpr uint32_t SM_BAR = SM_MISC;
constexpr uint32_t SM_B1 = SM_MISC + 512;
constexpr uint32_t SM_GATE = SM_MISC + 2304;
constexpr uint32_t SM_B2 = SM_MISC + 2816;
constexpr uint32_t B_FULL24 = SM_BAR + 0;
constexpr uint32_t B_EMPTY24 = SM_BAR + 64;
constexpr uint32_t B_FULL32 = SM_BAR + 128;
constexpr uint32_t B_EMPTY32 = SM_BAR + 176;
constexpr uint32_t B_DUMP = SM_BAR + 224;
constexpr uint32_t B_SFREE = SM_BAR + 256;
constexpr uint32_t B_GATES = SM_BAR + 264;
constexpr uint32_t B_SLO = SM_BAR + 272;
constexpr uint32_t B_FLAG = SM_BAR + 288;
constexpr uint32_t B_WPHI = SM_BAR + 280;

struct Params {
  CUtensorMap xa, y, h, o, wqkv, wqkv32, w1a, w1b, w2, wo, wphi, out;
  const __nv_bfloat16 *A_x, *b1, *b2, *gate_w;
  __nv_bfloat16 *py, *ph, *po;
};

__device__ __forceinline__ uint32_t smem_u32(const void* p) { return (uint32_t)__cvta_generic_to_shared(p); }
__device__ __forceinline__ void mbar_init(uint32_t bar, uint32_t cnt) {
  asm volatile("mbarrier.init.shared::cta.b64 [%0], %1;" ::"r"(bar), "r"(cnt) : "memory");
}
__device__ __forceinline__ void mbar_expect_tx(uint32_t bar, uint32_t bytes) {
  asm volatile("mbarrier.arrive.expect_tx.shared::cta.b64 _, [%0], %1;" ::"r"(bar), "r"(bytes) : "memory");
}
__device__ __forceinline__ void mbar_arrive(uint32_t bar) {
  asm volatile("mbarrier.arrive.shared::cta.b64 _, [%0];" ::"r"(bar) : "memory");
}
__device__ __forceinline__ void mbar_arrive_cluster(uint32_t bar, uint32_t cta) {
  asm volatile(
      "{\n.reg .b32 ra;\nmapa.shared::cluster.u32 ra, %0, %1;\n"
      "mbarrier.arrive.shared::cluster.b64 _, [ra];\n}" ::"r"(bar), "r"(cta) : "memory");
}
__device__ __forceinline__ void mbar_wait(uint32_t bar, uint32_t parity) {
  asm volatile(
      "{\n.reg .pred p;\n.reg .u32 it;\nmov.u32 it, 0;\n"
      "MW_LOOP:\nmbarrier.try_wait.parity.shared::cta.b64 p, [%0], %1;\n@p bra MW_DONE;\n"
      "add.u32 it, it, 1;\nsetp.lt.u32 p, it, 4194304;\n@p bra MW_LOOP;\ntrap;\nMW_DONE:\n}" ::"r"(bar), "r"(parity) : "memory");
}
__device__ __forceinline__ void mbar_wait_sleep(uint32_t bar, uint32_t parity) {
  asm volatile(
      "{\n.reg .pred p;\n.reg .u32 it;\nmov.u32 it, 0;\n"
      "MZ_LOOP:\nmbarrier.try_wait.parity.shared::cta.b64 p, [%0], %1, 20000;\n@p bra MZ_DONE;\n"
      "add.u32 it, it, 1;\nsetp.lt.u32 p, it, 4194304;\n@p bra MZ_LOOP;\ntrap;\nMZ_DONE:\n}" ::"r"(bar), "r"(parity) : "memory");
}
__device__ __forceinline__ bool mbar_test(uint32_t bar, uint32_t parity) {
  uint32_t ok;
  asm volatile("{\n.reg .pred p;\nmbarrier.test_wait.parity.shared::cta.b64 p, [%1], %2;\nselp.u32 %0, 1, 0, p;\n}"
               : "=r"(ok) : "r"(bar), "r"(parity) : "memory");
  return ok != 0;
}
__device__ __forceinline__ void wait_flag(const uint32_t* p, uint32_t target) {
  uint32_t it = 0;
  while (true) {
    uint32_t v;
    asm volatile("ld.acquire.gpu.global.u32 %0, [%1];" : "=r"(v) : "l"(p) : "memory");
    if ((int32_t)(v - target) >= 0) break;
    __nanosleep(50);
    if (++it > (1u << 22)) __trap();
  }
}
__device__ __forceinline__ uint32_t load_epoch() {
  uint32_t done;
  asm volatile("ld.relaxed.gpu.global.u32 %0, [%1];" : "=r"(done) : "l"(g_cnt + C_DONE * 32) : "memory");
  return done / NCTA + 1;
}
__device__ __forceinline__ void signal_flag(uint32_t* p) {
  asm volatile("red.release.gpu.global.add.u32 [%0], 1;" ::"l"(p) : "memory");
}
__device__ __forceinline__ void fence_async_all() { asm volatile("fence.proxy.async.global;" ::: "memory"); }
__device__ __forceinline__ void fence_async_smem() { asm volatile("fence.proxy.async.shared::cta;" ::: "memory"); }
__device__ __forceinline__ void tma_2d(uint32_t dst, const CUtensorMap* m, uint32_t bar, int c0, int c1) {
  asm volatile(
      "cp.async.bulk.tensor.2d.shared::cluster.global.mbarrier::complete_tx::bytes [%0], [%1, {%3, %4}], [%2];" ::"r"(dst),
      "l"(m), "r"(bar), "r"(c0), "r"(c1) : "memory");
}
__device__ __forceinline__ void tma_2d_mc(uint32_t dst, const CUtensorMap* m, uint32_t bar, int c0, int c1) {
  asm volatile(
      "cp.async.bulk.tensor.2d.shared::cluster.global.mbarrier::complete_tx::bytes.multicast::cluster [%0], [%1, {%3, "
      "%4}], [%2], %5;" ::"r"(dst),
      "l"(m), "r"(bar), "r"(c0), "r"(c1), "h"((uint16_t)3) : "memory");
}
__device__ __forceinline__ void tma_3d(uint32_t dst, const CUtensorMap* m, uint32_t bar, int c0, int c1, int c2) {
  asm volatile(
      "cp.async.bulk.tensor.3d.shared::cluster.global.mbarrier::complete_tx::bytes [%0], [%1, {%3, %4, %5}], [%2];" ::"r"(dst),
      "l"(m), "r"(bar), "r"(c0), "r"(c1), "r"(c2) : "memory");
}
__device__ __forceinline__ void tma_store_2d(const CUtensorMap* m, uint32_t src, int c0, int c1) {
  asm volatile("cp.async.bulk.tensor.2d.global.shared::cta.bulk_group [%0, {%2, %3}], [%1];" ::"l"(m), "r"(src), "r"(c0),
               "r"(c1) : "memory");
}
__device__ __forceinline__ void prefetch_tmap(const CUtensorMap* m) {
  asm volatile("prefetch.tensormap [%0];" ::"l"(m) : "memory");
}
__device__ __forceinline__ bool elect_one() {
  uint32_t pred = 0, laneid = 0;
  asm volatile(
      "{\n.reg .b32 rx;\n.reg .pred px;\nelect.sync rx|px, %2;\n@px mov.s32 %1, 1;\nmov.s32 %0, rx;\n}\n"
      : "+r"(laneid), "+r"(pred) : "r"(0xFFFFFFFFu));
  return pred != 0;
}
__device__ __forceinline__ void wg_fence() { asm volatile("wgmma.fence.sync.aligned;" ::: "memory"); }
__device__ __forceinline__ void wg_commit() { asm volatile("wgmma.commit_group.sync.aligned;" ::: "memory"); }
template <int N>
__device__ __forceinline__ void wg_wait() { asm volatile("wgmma.wait_group.sync.aligned %0;" ::"n"(N) : "memory"); }
__device__ __forceinline__ void epi_bar() { asm volatile("bar.sync 1, 128;" ::: "memory"); }
__device__ __forceinline__ uint32_t pack_bf16(float lo, float hi) {
  uint32_t r;
  asm("cvt.rn.bf16x2.f32 %0, %1, %2;" : "=r"(r) : "f"(hi), "f"(lo));
  return r;
}
__device__ __forceinline__ float bf_lo(uint32_t v) { return __uint_as_float(v << 16); }
__device__ __forceinline__ float bf_hi(uint32_t v) { return __uint_as_float(v & 0xffff0000u); }
__device__ __forceinline__ float ex2f(float x) {
  float r;
  asm("ex2.approx.ftz.f32 %0, %1;" : "=f"(r) : "f"(x));
  return r;
}
__device__ __forceinline__ float rcpf(float x) {
  float r;
  asm("rcp.approx.ftz.f32 %0, %1;" : "=f"(r) : "f"(x));
  return r;
}
__device__ __forceinline__ float tanhf_hw(float x) {
  float r;
  asm("tanh.approx.f32 %0, %1;" : "=f"(r) : "f"(x));
  return r;
}
__device__ __forceinline__ void stsm_x4(uint32_t addr, uint32_t a, uint32_t b, uint32_t c, uint32_t d) {
  asm volatile("stmatrix.sync.aligned.m8n8.x4.shared.b16 [%0], {%1, %2, %3, %4};" ::"r"(addr), "r"(a), "r"(b), "r"(c),
               "r"(d) : "memory");
}
__device__ __forceinline__ float lds_f32(uint32_t a) {
  float v;
  asm volatile("ld.shared.f32 %0, [%1];" : "=f"(v) : "r"(a) : "memory");
  return v;
}
__device__ __forceinline__ void sts_f32(uint32_t a, float v) { asm volatile("st.shared.f32 [%0], %1;" ::"r"(a), "f"(v) : "memory"); }
__device__ __forceinline__ uint64_t make_desc(uint32_t addr, uint32_t lbo, uint32_t sbo, uint32_t swz) {
  return (uint64_t)((addr & 0x3FFFF) >> 4) | ((uint64_t)(lbo >> 4) << 16) | ((uint64_t)(sbo >> 4) << 32) |
         ((uint64_t)swz << 62);
}
template <int N>
__device__ __forceinline__ void fence_regs(float (&d)[N]) {
#pragma unroll
  for (int i = 0; i < N; i++) asm volatile("" : "+f"(d[i])::"memory");
}

__device__ __forceinline__ void wgmma_ss_n192(float (&d)[96], uint64_t da, uint64_t db, int scale_d) {
  asm volatile("{\n.reg .pred p;\nsetp.ne.b32 p, %98, 0;\n"
    "wgmma.mma_async.sync.aligned.m64n192k16.f32.bf16.bf16 "
    "{%0, %1, %2, %3, %4, %5, %6, %7, %8, %9, %10, %11, %12, %13, %14, %15, %16, %17, %18, %19, %20, %21, %22, %23, %24, %25, %26, %27, %28, %29, %30, %31, %32, %33, %34, %35, %36, %37, %38, %39, %40, %41, %42, %43, %44, %45, %46, %47, %48, %49, %50, %51, %52, %53, %54, %55, %56, %57, %58, %59, %60, %61, %62, %63, %64, %65, %66, %67, %68, %69, %70, %71, %72, %73, %74, %75, %76, %77, %78, %79, %80, %81, %82, %83, %84, %85, %86, %87, %88, %89, %90, %91, %92, %93, %94, %95}, %96, %97, p, 1, 1, 0, 1;\n}\n"
    : "+f"(d[0]), "+f"(d[1]), "+f"(d[2]), "+f"(d[3]), "+f"(d[4]), "+f"(d[5]), "+f"(d[6]), "+f"(d[7]), "+f"(d[8]), "+f"(d[9]), "+f"(d[10]), "+f"(d[11]), "+f"(d[12]), "+f"(d[13]), "+f"(d[14]), "+f"(d[15]), "+f"(d[16]), "+f"(d[17]), "+f"(d[18]), "+f"(d[19]), "+f"(d[20]), "+f"(d[21]), "+f"(d[22]), "+f"(d[23]), "+f"(d[24]), "+f"(d[25]), "+f"(d[26]), "+f"(d[27]), "+f"(d[28]), "+f"(d[29]), "+f"(d[30]), "+f"(d[31]), "+f"(d[32]), "+f"(d[33]), "+f"(d[34]), "+f"(d[35]), "+f"(d[36]), "+f"(d[37]), "+f"(d[38]), "+f"(d[39]), "+f"(d[40]), "+f"(d[41]), "+f"(d[42]), "+f"(d[43]), "+f"(d[44]), "+f"(d[45]), "+f"(d[46]), "+f"(d[47]), "+f"(d[48]), "+f"(d[49]), "+f"(d[50]), "+f"(d[51]), "+f"(d[52]), "+f"(d[53]), "+f"(d[54]), "+f"(d[55]), "+f"(d[56]), "+f"(d[57]), "+f"(d[58]), "+f"(d[59]), "+f"(d[60]), "+f"(d[61]), "+f"(d[62]), "+f"(d[63]), "+f"(d[64]), "+f"(d[65]), "+f"(d[66]), "+f"(d[67]), "+f"(d[68]), "+f"(d[69]), "+f"(d[70]), "+f"(d[71]), "+f"(d[72]), "+f"(d[73]), "+f"(d[74]), "+f"(d[75]), "+f"(d[76]), "+f"(d[77]), "+f"(d[78]), "+f"(d[79]), "+f"(d[80]), "+f"(d[81]), "+f"(d[82]), "+f"(d[83]), "+f"(d[84]), "+f"(d[85]), "+f"(d[86]), "+f"(d[87]), "+f"(d[88]), "+f"(d[89]), "+f"(d[90]), "+f"(d[91]), "+f"(d[92]), "+f"(d[93]), "+f"(d[94]), "+f"(d[95])
    : "l"(da), "l"(db), "r"(scale_d));
}
__device__ __forceinline__ void wgmma_ss_n128(float (&d)[64], uint64_t da, uint64_t db, int scale_d) {
  asm volatile("{\n.reg .pred p;\nsetp.ne.b32 p, %66, 0;\n"
    "wgmma.mma_async.sync.aligned.m64n128k16.f32.bf16.bf16 "
    "{%0, %1, %2, %3, %4, %5, %6, %7, %8, %9, %10, %11, %12, %13, %14, %15, %16, %17, %18, %19, %20, %21, %22, %23, %24, %25, %26, %27, %28, %29, %30, %31, %32, %33, %34, %35, %36, %37, %38, %39, %40, %41, %42, %43, %44, %45, %46, %47, %48, %49, %50, %51, %52, %53, %54, %55, %56, %57, %58, %59, %60, %61, %62, %63}, %64, %65, p, 1, 1, 0, 1;\n}\n"
    : "+f"(d[0]), "+f"(d[1]), "+f"(d[2]), "+f"(d[3]), "+f"(d[4]), "+f"(d[5]), "+f"(d[6]), "+f"(d[7]), "+f"(d[8]), "+f"(d[9]), "+f"(d[10]), "+f"(d[11]), "+f"(d[12]), "+f"(d[13]), "+f"(d[14]), "+f"(d[15]), "+f"(d[16]), "+f"(d[17]), "+f"(d[18]), "+f"(d[19]), "+f"(d[20]), "+f"(d[21]), "+f"(d[22]), "+f"(d[23]), "+f"(d[24]), "+f"(d[25]), "+f"(d[26]), "+f"(d[27]), "+f"(d[28]), "+f"(d[29]), "+f"(d[30]), "+f"(d[31]), "+f"(d[32]), "+f"(d[33]), "+f"(d[34]), "+f"(d[35]), "+f"(d[36]), "+f"(d[37]), "+f"(d[38]), "+f"(d[39]), "+f"(d[40]), "+f"(d[41]), "+f"(d[42]), "+f"(d[43]), "+f"(d[44]), "+f"(d[45]), "+f"(d[46]), "+f"(d[47]), "+f"(d[48]), "+f"(d[49]), "+f"(d[50]), "+f"(d[51]), "+f"(d[52]), "+f"(d[53]), "+f"(d[54]), "+f"(d[55]), "+f"(d[56]), "+f"(d[57]), "+f"(d[58]), "+f"(d[59]), "+f"(d[60]), "+f"(d[61]), "+f"(d[62]), "+f"(d[63])
    : "l"(da), "l"(db), "r"(scale_d));
}
__device__ __forceinline__ void wgmma_ss_n40_tt(float (&d)[20], uint64_t da, uint64_t db, int scale_d) {
  asm volatile("{\n.reg .pred p;\nsetp.ne.b32 p, %22, 0;\n"
    "wgmma.mma_async.sync.aligned.m64n40k16.f32.bf16.bf16 "
    "{%0, %1, %2, %3, %4, %5, %6, %7, %8, %9, %10, %11, %12, %13, %14, %15, %16, %17, %18, %19}, %20, %21, p, 1, 1, 1, 1;\n}\n"
    : "+f"(d[0]), "+f"(d[1]), "+f"(d[2]), "+f"(d[3]), "+f"(d[4]), "+f"(d[5]), "+f"(d[6]), "+f"(d[7]), "+f"(d[8]), "+f"(d[9]), "+f"(d[10]), "+f"(d[11]), "+f"(d[12]), "+f"(d[13]), "+f"(d[14]), "+f"(d[15]), "+f"(d[16]), "+f"(d[17]), "+f"(d[18]), "+f"(d[19])
    : "l"(da), "l"(db), "r"(scale_d));
}
__device__ __forceinline__ void wgmma_rs_n32(float (&d)[16], uint32_t a0, uint32_t a1, uint32_t a2, uint32_t a3, uint64_t db, int scale_d) {
  asm volatile("{\n.reg .pred p;\nsetp.ne.b32 p, %21, 0;\n"
    "wgmma.mma_async.sync.aligned.m64n32k16.f32.bf16.bf16 "
    "{%0, %1, %2, %3, %4, %5, %6, %7, %8, %9, %10, %11, %12, %13, %14, %15}, {%16, %17, %18, %19}, %20, p, 1, 1, 1;\n}\n"
    : "+f"(d[0]), "+f"(d[1]), "+f"(d[2]), "+f"(d[3]), "+f"(d[4]), "+f"(d[5]), "+f"(d[6]), "+f"(d[7]), "+f"(d[8]), "+f"(d[9]), "+f"(d[10]), "+f"(d[11]), "+f"(d[12]), "+f"(d[13]), "+f"(d[14]), "+f"(d[15])
    : "r"(a0), "r"(a1), "r"(a2), "r"(a3), "l"(db), "r"(scale_d));
}
__device__ __forceinline__ void wgmma_ss_n32_nt(float (&d)[16], uint64_t da, uint64_t db, int scale_d) {
  asm volatile("{\n.reg .pred p;\nsetp.ne.b32 p, %18, 0;\n"
    "wgmma.mma_async.sync.aligned.m64n32k16.f32.bf16.bf16 "
    "{%0, %1, %2, %3, %4, %5, %6, %7, %8, %9, %10, %11, %12, %13, %14, %15}, %16, %17, p, 1, 1, 0, 1;\n}\n"
    : "+f"(d[0]), "+f"(d[1]), "+f"(d[2]), "+f"(d[3]), "+f"(d[4]), "+f"(d[5]), "+f"(d[6]), "+f"(d[7]), "+f"(d[8]), "+f"(d[9]), "+f"(d[10]), "+f"(d[11]), "+f"(d[12]), "+f"(d[13]), "+f"(d[14]), "+f"(d[15])
    : "l"(da), "l"(db), "r"(scale_d));
}


template <int N>
struct MMA;
__device__ __forceinline__ uint64_t bdesc(uint32_t lo) { return ((uint64_t)0x40000040u << 32) | lo; }
template <>
struct MMA<256> {
  static __device__ __forceinline__ void run(float (&d)[128], uint64_t a, uint32_t b, int s, uint32_t gs) {
    wgmma_ss_n128(*reinterpret_cast<float(*)[64]>(&d[0]), a, bdesc(b), s);
    wgmma_ss_n128(*reinterpret_cast<float(*)[64]>(&d[64]), a, bdesc(b + 2 * gs), s);
  }
};
template <>
struct MMA<192> {
  static __device__ __forceinline__ void run(float (&d)[96], uint64_t a, uint32_t b, int s, uint32_t) { wgmma_ss_n192(d, a, bdesc(b), s); }
};
template <>
struct MMA<128> {
  static __device__ __forceinline__ void run(float (&d)[64], uint64_t a, uint32_t b, int s, uint32_t) { wgmma_ss_n128(d, a, bdesc(b), s); }
};

__device__ __forceinline__ uint32_t offB2(int s) { return s * 16384 + (s >= 6 ? 49152 : 0); }
__device__ __forceinline__ uint32_t offA2(int s) { return 98304 + (s >> 1) * 16384 + (s >= 6 ? 32768 : 0); }
__device__ __forceinline__ uint32_t off4(int s) { return (s ^ ((s >> 1) & 1)) * 32768; }
template <int NS, int START, int COUNT, int STEP, class F>
__device__ __forceinline__ void ring_loop(F&& f) {
  int s = START;
#pragma unroll 1
  for (int i = 0; i < COUNT; i++) {
    f(s);
    s += STEP;
    if (s == NS) s = 0;
  }
}
struct LoopState { bool ready; };
template <int N, int KS, int NS, int START, int COUNT, bool CONT, bool CHAIN_IN = false, bool CHAIN_OUT = false, int PREV0 = 0>
__device__ __forceinline__ void mainloop(float (&acc)[N / 2], uint32_t& ph, uint32_t sb, int w, int t, LoopState& ls) {
  constexpr uint32_t FULLB = KS == 2 ? B_FULL24 : B_FULL32, EMPTYB = KS == 2 ? B_EMPTY24 : B_EMPTY32;
  constexpr bool EARLY = KS == 4;
  uint32_t dA0 = (uint32_t)make_desc(1024 + SM_RING + w * 8192, 16, 1024, 1);
  constexpr uint32_t dB0 = ((1024 + SM_RING) >> 4) | ((KS * 2048 >> 4) << 16);
  auto desc = [](uint32_t lo) { return ((uint64_t)0x40000040u << 32) | lo; };
  const bool rel = (t & 95) == 0;
  uint32_t remote;
  asm("mapa.shared::cluster.u32 %0, %1, %2;" : "=r"(remote) : "r"(sb + EMPTYB), "r"((t >> 5) & 1));
  auto release = [&](int s) {
    if (rel) asm volatile("mbarrier.arrive.shared::cluster.b64 _, [%0];" ::"r"(remote + 8 * s) : "memory");
  };
  bool ready = CHAIN_IN ? ls.ready : mbar_test(sb + FULLB + 8 * START, ph);
  bool pending = CHAIN_IN;
  bool first = !CONT;
  auto step = [&](const int S, const bool first_of_call = false) {
    const int PREV = (CHAIN_IN && first_of_call) ? PREV0 : (S + NS - 1) % NS, NEXT = (S + 1) % NS;
    if (__builtin_expect(!ready, 0)) {
      if (pending) {
        wg_wait<0>();
        release(PREV);
        pending = false;
      }
      mbar_wait(sb + FULLB + 8 * S, ph);
    }
    const uint32_t da = dA0 + ((KS == 2 ? offA2(S) + (S & 1) * 64 : off4(S)) >> 4);
    const uint32_t db = dB0 + ((KS == 2 ? offB2(S) : off4(S) + 16384) >> 4);
    wg_fence();
    if constexpr (EARLY) {
      MMA<N>::run(acc, desc(da), db, first ? 0 : 1, KS * 128);
      wg_commit();
      if (pending) {
        wg_wait<1>();
        release(PREV);
      }
#pragma unroll
      for (int k = 1; k < KS; k++) MMA<N>::run(acc, desc(da + k * 2), db + k * 128, 1, KS * 128);
      wg_commit();
      if (NEXT == 0) ph ^= 1;
      ready = mbar_test(sb + FULLB + 8 * NEXT, ph);
    } else {
#pragma unroll
      for (int k = 0; k < KS; k++) MMA<N>::run(acc, desc(da + k * 2), db + k * 128, (k == 0 && first) ? 0 : 1, KS * 128);
      wg_commit();
      if (NEXT == 0) ph ^= 1;
      ready = mbar_test(sb + FULLB + 8 * NEXT, ph);
      if (pending) {
        wg_wait<1>();
        release(PREV);
      }
    }
    pending = true;
    first = false;
  };
  constexpr int LEAD = START == 0 ? 0 : (NS - START < COUNT ? NS - START : COUNT);
  constexpr int ROUNDS = (COUNT - LEAD) / NS, TAIL = (COUNT - LEAD) % NS;
  static_assert(!CHAIN_IN || PREV0 == (START + NS - 1) % NS || START == 0, "bad chain");
  if constexpr (CHAIN_IN && PREV0 != (START + NS - 1) % NS) {
#pragma unroll
    for (int i = 0; i < NS; i++) step(i, i == 0);
  }
  constexpr int PEEL = (CHAIN_IN && PREV0 != (START + NS - 1) % NS) ? 1 : 0;
#pragma unroll
  for (int i = 0; i < LEAD; i++) step(START + i);
#pragma unroll 1
  for (int r = 0; r < ROUNDS - PEEL; r++) {
    dA0 = __shfl_sync(0xffffffffu, dA0, 0);
#pragma unroll
    for (int i = 0; i < NS; i++) step(i);
  }
#pragma unroll
  for (int i = 0; i < TAIL; i++) step(i);
  if constexpr (CHAIN_OUT) {
    ls.ready = ready;
  } else {
    wg_wait<0>();
    release((START + COUNT - 1) % NS);
    fence_regs(acc);
  }
}

__device__ __forceinline__ uint32_t bmax2(uint32_t a, uint32_t b) { uint32_t r; asm("max.bf16x2 %0, %1, %2;" : "=r"(r) : "r"(a), "r"(b)); return r; }
__device__ __forceinline__ uint32_t bmin2(uint32_t a, uint32_t b) { uint32_t r; asm("min.bf16x2 %0, %1, %2;" : "=r"(r) : "r"(a), "r"(b)); return r; }
__device__ __forceinline__ float4 lds128f(uint32_t a) {
  float4 v;
  asm volatile("ld.shared.v4.f32 {%0, %1, %2, %3}, [%4];" : "=f"(v.x), "=f"(v.y), "=f"(v.z), "=f"(v.w) : "r"(a));
  return v;
}
template <bool DEN>
__device__ __forceinline__ float hedgehog_row(const uint32_t (&w)[16], uint32_t (&out)[32], uint32_t zaddr) {
  constexpr float L2E = 1.4426950408889634f;
  uint32_t mx2[8], mn2[8];
#pragma unroll
  for (int i = 0; i < 8; i++) { mx2[i] = bmax2(w[2 * i], w[2 * i + 1]); mn2[i] = bmin2(w[2 * i], w[2 * i + 1]); }
#pragma unroll
  for (int st = 4; st > 0; st >>= 1)
#pragma unroll
    for (int i = 0; i < st; i++) { mx2[i] = bmax2(mx2[i], mx2[i + st]); mn2[i] = bmin2(mn2[i], mn2[i + st]); }
  const float a = -fmaxf(bf_lo(mx2[0]), bf_hi(mx2[0])) * L2E;
  const float b = fminf(bf_lo(mn2[0]), bf_hi(mn2[0])) * L2E;
  float den = 0.f;
#pragma unroll
  for (int sgn = 0; sgn < 2; sgn++) {
    const float mul = sgn ? -L2E : L2E, off = sgn ? b : a;
    float e[32];
#pragma unroll
    for (int i = 0; i < 16; i++) {
      e[2 * i] = ex2f(fmaf(bf_lo(w[i]), mul, off));
      e[2 * i + 1] = ex2f(fmaf(bf_hi(w[i]), mul, off));
    }
    float s0 = 0.f, s1 = 0.f, s2 = 0.f, s3 = 0.f;
#pragma unroll
    for (int i = 0; i < 8; i++) { s0 += e[4 * i]; s1 += e[4 * i + 1]; s2 += e[4 * i + 2]; s3 += e[4 * i + 3]; }
    const float r = rcpf((s0 + s1) + (s2 + s3));
    if (DEN) {
      float d0 = 0.f, d1 = 0.f, d2 = 0.f, d3 = 0.f;
#pragma unroll
      for (int i = 0; i < 8; i++) {
        const float4 z = lds128f(zaddr + sgn * 128 + i * 16);
        d0 = fmaf(e[4 * i], z.x, d0); d1 = fmaf(e[4 * i + 1], z.y, d1);
        d2 = fmaf(e[4 * i + 2], z.z, d2); d3 = fmaf(e[4 * i + 3], z.w, d3);
      }
      den = fmaf((d0 + d1) + (d2 + d3), r, den);
    }
#pragma unroll
    for (int i = 0; i < 16; i++) out[16 * sgn + i] = pack_bf16(e[2 * i] * r, e[2 * i + 1] * r);
  }
  return den;
}
__device__ __forceinline__ uint4 lds128(uint32_t a) {
  uint4 v;
  asm volatile("ld.shared.v4.u32 {%0, %1, %2, %3}, [%4];" : "=r"(v.x), "=r"(v.y), "=r"(v.z), "=r"(v.w) : "r"(a) : "memory");
  return v;
}
__device__ __forceinline__ void sts128(uint32_t a, uint32_t x, uint32_t y, uint32_t z, uint32_t w) {
  asm volatile("st.shared.v4.u32 [%0], {%1, %2, %3, %4};" ::"r"(a), "r"(x), "r"(y), "r"(z), "r"(w) : "memory");
}

__device__ __forceinline__ float gelu2(float v) {
  constexpr float C0 = 0.7978845608028654f, C1 = 0.7978845608028654f * 0.044715f;
  const float u = v * fmaf(v * v, C1, C0);
  return fmaf(v, tanhf_hw(u), v);
}
__device__ __forceinline__ uint32_t badd2(uint32_t a, uint32_t b) { uint32_t r; asm("add.rn.bf16x2 %0, %1, %2;" : "=r"(r) : "r"(a), "r"(b)); return r; }
__device__ __forceinline__ uint4 gelu8(uint4 x, uint4 b) {
  const uint32_t v0 = badd2(x.x, b.x), v1 = badd2(x.y, b.y), v2 = badd2(x.z, b.z), v3 = badd2(x.w, b.w);
  uint4 r;
  r.x = pack_bf16(gelu2(bf_lo(v0)), gelu2(bf_hi(v0)));
  r.y = pack_bf16(gelu2(bf_lo(v1)), gelu2(bf_hi(v1)));
  r.z = pack_bf16(gelu2(bf_lo(v2)), gelu2(bf_hi(v2)));
  r.w = pack_bf16(gelu2(bf_lo(v3)), gelu2(bf_hi(v3)));
  return r;
}
__device__ __forceinline__ float warp_sum(float v) {
#pragma unroll
  for (int o = 16; o > 0; o >>= 1) v += __shfl_xor_sync(0xffffffffu, v, o);
  return v;
}
#define CTA_CONTEXT()                                                                        \
  uint32_t cta_u, rank_u;                                                                    \
  asm volatile("mov.u32 %0, %%ctaid.x;" : "=r"(cta_u));                                      \
  asm volatile("mov.u32 %0, %%cluster_ctarank;" : "=r"(rank_u));                             \
  const int cta = (int)cta_u, rank = (int)rank_u, cl = cta >> 1;                             \
  const uint32_t sb = (rank_u << 24) + 1024u;      \
  const int m = CL2M(cl), nn = CL2P(cl) * 2 + rank, row0 = m * 128;                          \
  (void)cta; (void)nn; (void)row0; (void)sb;
#define CL2M(cl) ((((cl) >> 3) * 2) + ((cl) & 1))
#define CL2P(cl) (((cl) >> 1) & 3)

__global__ void __cluster_dims__(2, 1, 1) __launch_bounds__(512, 1) fused_kernel(const __grid_constant__ Params P) {
  extern __shared__ __align__(1024) uint8_t smem_raw[];
  const int tid = threadIdx.x;
  const int wg = __shfl_sync(0xffffffffu, tid >> 7, 0);
  const int t = tid & 127;
  {
  CTA_CONTEXT();
  if (tid < 32) {
    if (elect_one()) {
      prefetch_tmap(&P.xa);
      prefetch_tmap(&P.wqkv32);
      if (sb != smem_u32(smem_raw)) __trap();
#pragma unroll
      for (int s = 0; s < 8; s++) mbar_init(sb + B_FULL24 + 8 * s, 1);
      asm volatile("fence.mbarrier_init.release.cluster;" ::: "memory");
      fence_async_smem();
#pragma unroll
      for (int i = 0; i < 2; i++) {
        const uint32_t fb = sb + B_FULL24 + 8 * i, bb = sb + SM_RING + offB2(i);
        mbar_expect_tx(fb, (i & 1) ? 16384 : 32768);
        if (!(i & 1)) {
          tma_2d(sb + SM_RING + offA2(i), &P.xa, fb, i * 32, row0);
          tma_2d(sb + SM_RING + offA2(i) + 8192, &P.xa, fb, i * 32, row0 + 64);
        }
        tma_3d(bb, &P.wqkv32, fb, 0, i * 32, 16 + 2 * nn);
        tma_3d(bb + 8192, &P.wqkv32, fb, 0, i * 32, 32 + 2 * nn);
      }
    }
    __syncwarp();
  } else if (tid == 32) {
    for (int s = 0; s < 8; s++) mbar_init(sb + B_EMPTY24 + 8 * s, 4);
    for (int s = 0; s < NS32; s++) { mbar_init(sb + B_FULL32 + 8 * s, 1); mbar_init(sb + B_EMPTY32 + 8 * s, 4); }
    for (int s = 0; s < 4; s++) mbar_init(sb + B_DUMP + 8 * s, 256);
    mbar_init(sb + B_SFREE, 128);
    mbar_init(sb + B_GATES, 128);
    mbar_init(sb + B_SLO, 2);
    mbar_init(sb + B_WPHI, 1);
    for (int s = 0; s < 4; s++) mbar_init(sb + B_FLAG + 8 * s, 1);
    asm volatile("fence.mbarrier_init.release.cluster;" ::: "memory");
  }
  }
  __syncthreads();
  asm volatile("barrier.cluster.arrive.relaxed.aligned;" ::: "memory");

  if (wg == 0) {
    asm volatile("setmaxnreg.dec.sync.aligned.u32 40;");
    CTA_CONTEXT();
    if (tid < 32 && elect_one()) {
#pragma unroll
      for (int i = 2; i < 8; i++) {
        const uint32_t fb = sb + B_FULL24 + 8 * i, bb = sb + SM_RING + offB2(i);
        mbar_expect_tx(fb, (i & 1) ? 16384 : 32768);
        if (!(i & 1)) {
          tma_2d(sb + SM_RING + offA2(i), &P.xa, fb, i * 32, row0);
          tma_2d(sb + SM_RING + offA2(i) + 8192, &P.xa, fb, i * 32, row0 + 64);
        }
        tma_3d(bb, &P.wqkv32, fb, 0, i * 32, 16 + 2 * nn);
        tma_3d(bb + 8192, &P.wqkv32, fb, 0, i * 32, 32 + 2 * nn);
      }
    }
    __syncwarp();
    asm volatile("barrier.cluster.wait.acquire.aligned;" ::: "memory");
    if ((tid >> 5) == 3 && elect_one()) {
      const uint32_t ep = load_epoch();
      wait_flag(g_cnt + (C_Y + m) * 32, ep * 8);
      mbar_arrive(sb + B_FLAG + 0);
      wait_flag(g_cnt + (C_H1 + m) * 32, ep * 8);
      wait_flag(g_cnt + (C_SYNC + nn) * 32, ep * 16);
      mbar_arrive(sb + B_FLAG + 8);
      wait_flag(g_cnt + (C_H2 + m) * 32, ep * 8);
      mbar_arrive(sb + B_FLAG + 16);
      wait_flag(g_cnt + (C_O + m) * 32, ep * 8);
      mbar_arrive(sb + B_FLAG + 24);
    }
    if ((tid >> 5) == 2 && elect_one()) {
      prefetch_tmap(&P.y); prefetch_tmap(&P.wqkv); prefetch_tmap(&P.w1a); prefetch_tmap(&P.w1b); prefetch_tmap(&P.h);
      prefetch_tmap(&P.w2); prefetch_tmap(&P.o); prefetch_tmap(&P.wo);
      const int rowh = row0 + rank * 64;
      uint32_t ph24 = 0;
      {
        constexpr uint32_t F2E = B_FULL24 - B_EMPTY24;
        int k = 0;
        auto pair = [&](const int tile, const int NS, const int S) {
          const uint32_t eb = sb + B_EMPTY24 + 8 * S, fb = eb + F2E;
          const uint32_t bb = sb + SM_RING + offB2(S), ab = sb + SM_RING + offA2(S) + rank * 8192;
          const uint32_t bbytes = tile == 2 ? 12288 : 16384;
          mbar_wait(eb, ph24);
          mbar_expect_tx(fb, 16384 + bbytes);
          if (tile == 0) {
            tma_3d(bb, &P.wqkv32, fb, 0, k, 16 + 2 * nn);
            tma_3d(bb + 8192, &P.wqkv32, fb, 0, k, 32 + 2 * nn);
          } else if (tile == 1) tma_3d(bb, &P.w1a, fb, 0, k, 7 * nn);
          else tma_3d(bb, &P.w1b, fb, 0, k, 7 * nn + 4);
          mbar_wait(eb + 8, ph24);
          tma_2d_mc(ab, tile == 0 ? &P.xa : &P.y, fb, k, rowh);
          mbar_expect_tx(fb + 8, bbytes);
          if (tile == 0) {
            tma_3d(bb + 16384, &P.wqkv32, fb + 8, 0, k + 32, 16 + 2 * nn);
            tma_3d(bb + 16384 + 8192, &P.wqkv32, fb + 8, 0, k + 32, 32 + 2 * nn);
          } else if (tile == 1) tma_3d(bb + 16384, &P.w1a, fb + 8, 0, k + 32, 7 * nn);
          else tma_3d(bb + 16384, &P.w1b, fb + 8, 0, k + 32, 7 * nn + 4);
          k += 64;
          if (S + 2 == NS) ph24 ^= 1;
        };
        k = 4 * 64;
        ring_loop<8, 0, 8, 2>([&](const int S) { pair(0, 8, S); });
        ring_loop<6, 0, 4, 2>([&](const int S) { pair(0, 6, S); });
        mbar_wait(sb + B_FLAG + 0, 0);
        fence_async_all();
        k = 0;
        ring_loop<6, 2, 16, 2>([&](const int S) { pair(1, 6, S); });
        k = 0;
        ring_loop<6, 4, 16, 2>([&](const int S) { pair(2, 6, S); });
      }
      uint32_t ph = 1;
      int col = 0;
      auto entry = [&](const int S, const CUtensorMap* ma, const CUtensorMap* mb, int bgroup) {
        const uint32_t fb = sb + B_FULL32 + 8 * S, sa = sb + SM_RING + off4(S);
        mbar_expect_tx(fb, 32768);
        tma_2d_mc(sa + rank * 8192, ma, fb, col, rowh);
        tma_3d(sa + 16384, mb, fb, 0, col, bgroup);
        if (S == NS32 - 1) ph ^= 1;
      };
#pragma unroll
      for (int j = 0; j < NS32; j++) {
        if (j == 0) mbar_wait(sb + B_EMPTY24 + 8 * 1, ph24);
        else if (j == 1) mbar_wait(sb + B_EMPTY24 + 8 * 3, ph24);
        else if (j == 3) mbar_wait(sb + B_EMPTY24 + 8 * 5, ph24);
        else if (j == 4) mbar_wait(sb + B_SLO, 0);
        entry(j, &P.xa, &P.wqkv, 2 * nn);
        col += 64;
      }
      ring_loop<NS32, 0, 11, 1>([&](const int S) {
        if (col == 13 * 64) asm volatile("red.relaxed.gpu.global.add.u32 [%0], 1;" ::"l"(g_cnt + (C_SYNC + nn) * 32) : "memory");
        mbar_wait(sb + B_EMPTY32 + 8 * S, ph);
        entry(S, &P.xa, &P.wqkv, 2 * nn);
        col += 64;
      });
      mbar_wait(sb + B_FLAG + 8, 0);
      fence_async_all();
      const int rot = 2 * (nn >> 1);
      col = 448 * (rot & 7);
      int sub = 0;
      ring_loop<NS32, 1, 32, 1>([&](const int S) {
        mbar_wait(sb + B_EMPTY32 + 8 * S, ph);
        entry(S, &P.h, &P.w2, 2 * nn);
        col += 64;
        if (++sub == 4) { sub = 0; col += 192; if (col == F_) col = 0; }
      });
      mbar_wait(sb + B_FLAG + 16, 0);
      fence_async_all();
      col = 256 + 448 * (rot & 7);
      ring_loop<NS32, 3, 24, 1>([&](const int S) {
        mbar_wait(sb + B_EMPTY32 + 8 * S, ph);
        entry(S, &P.h, &P.w2, 2 * nn);
        col += 64;
        if (++sub == 3) { sub = 0; col += 256; if (col > F_) col = 256; }
      });
      mbar_wait(sb + B_FLAG + 24, 0);
      fence_async_all();
      col = 128 * (rot & 7);
      ring_loop<NS32, 2, 16, 1>([&](const int S) {
        mbar_wait(sb + B_EMPTY32 + 8 * S, ph);
        entry(S, &P.o, &P.wo, 2 * nn);
        col = (col + 64) & (D_ - 1);
      });
      ring_loop<NS32, 3, NS32, 1>([&](const int S) {
        mbar_wait(sb + B_EMPTY32 + 8 * S, ph);
        if (S == NS32 - 1) ph ^= 1;
      });
    }
  } else if (wg <= 2) {
    asm volatile("setmaxnreg.inc.sync.aligned.u32 168;");
    CTA_CONTEXT();
    asm volatile("barrier.cluster.wait.acquire.aligned;" ::: "memory");
    const int w = wg - 1;
    const int warp = t >> 5, lane = t & 31, q = lane & 3;
    const int rloc = w * 64 + warp * 16 + (lane >> 2);
    const int srow = w * 64 + warp * 16 + ((lane >> 3) & 1) * 8 + (lane & 7);
    const uint32_t st_row = srow * 128, st_x = srow & 7, st_hi = lane >> 4;
    LoopState ls;
    {
      uint32_t ph = 0;
      {
        float acc[128];
        mainloop<256, 2, 8, 0, 24, false, false, true>(acc, ph, sb, w, t, ls);
        mainloop<256, 2, 6, 0, 8, true, true, false, 7>(acc, ph, sb, w, t, ls);
        {
          uint32_t kp[32], vp[32];
#pragma unroll
          for (int i = 0; i < 32; i++) {
            vp[i] = pack_bf16(acc[64 + 2 * i], acc[64 + 2 * i + 1]);
            asm volatile("" : "+r"(vp[i]));
          }
#pragma unroll
          for (int i = 0; i < 32; i++) kp[i] = pack_bf16(acc[2 * i], acc[2 * i + 1]);
          mbar_wait(sb + B_WPHI, 0);
          const uint64_t dW = make_desc(sb + SM_X, 16, 512, 2);
          float p[4][16];
          wg_fence();
#pragma unroll
          for (int h = 0; h < 4; h++) wgmma_rs_n32(p[h], kp[8 * h], kp[8 * h + 1], kp[8 * h + 2], kp[8 * h + 3], dW + h * 128, 0);
#pragma unroll
          for (int h = 0; h < 4; h++) wgmma_rs_n32(p[h], kp[8 * h + 4], kp[8 * h + 5], kp[8 * h + 6], kp[8 * h + 7], dW + h * 128 + 64, 1);
          wg_commit();
#pragma unroll
          for (int h = 0; h < 4; h++) {
            const uint32_t tb = sb + SM_STG + h * 16384 + st_row;
            stsm_x4(tb + (((0 + st_hi) ^ st_x) << 4), vp[8 * h], vp[8 * h + 1], vp[8 * h + 2], vp[8 * h + 3]);
            stsm_x4(tb + (((2 + st_hi) ^ st_x) << 4), vp[8 * h + 4], vp[8 * h + 5], vp[8 * h + 6], vp[8 * h + 7]);
          }
          wg_wait<0>();
#pragma unroll
          for (int h = 0; h < 4; h++) {
            fence_regs(p[h]);
            const uint32_t tb = sb + SM_STG + h * 16384 + st_row;
            stsm_x4(tb + (((4 + st_hi) ^ st_x) << 4), pack_bf16(p[h][0], p[h][1]), pack_bf16(p[h][2], p[h][3]),
                    pack_bf16(p[h][4], p[h][5]), pack_bf16(p[h][6], p[h][7]));
            stsm_x4(tb + (((6 + st_hi) ^ st_x) << 4), pack_bf16(p[h][8], p[h][9]), pack_bf16(p[h][10], p[h][11]),
                    pack_bf16(p[h][12], p[h][13]), pack_bf16(p[h][14], p[h][15]));
          }
          fence_async_smem();
          mbar_arrive(sb + B_DUMP + 0);
        }
      }
      {
        float acc[128];
        mainloop<256, 2, 6, 2, 32, false>(acc, ph, sb, w, t, ls);
        mbar_wait(sb + B_SFREE, 0);
#pragma unroll
        for (int i = 0; i < 16; i++)
          stsm_x4(sb + SM_STG + (i >> 2) * 16384 + st_row + (((2 * (i & 3) + st_hi) ^ st_x) << 4),
                  pack_bf16(acc[8 * i], acc[8 * i + 1]), pack_bf16(acc[8 * i + 2], acc[8 * i + 3]),
                  pack_bf16(acc[8 * i + 4], acc[8 * i + 5]), pack_bf16(acc[8 * i + 6], acc[8 * i + 7]));
        mbar_arrive(sb + B_DUMP + 8);
      }
      {
        float acc[96];
        mainloop<192, 2, 6, 4, 32, false>(acc, ph, sb, w, t, ls);
        mbar_wait(sb + B_SFREE, 1);
#pragma unroll
        for (int i = 0; i < 12; i++)
          stsm_x4(sb + SM_STGH + (i >> 2) * 16384 + st_row + (((2 * (i & 3) + st_hi) ^ st_x) << 4),
                  pack_bf16(acc[8 * i], acc[8 * i + 1]), pack_bf16(acc[8 * i + 2], acc[8 * i + 3]),
                  pack_bf16(acc[8 * i + 4], acc[8 * i + 5]), pack_bf16(acc[8 * i + 6], acc[8 * i + 7]));
        mbar_arrive(sb + B_DUMP + 16);
      }
    }
    {
      uint32_t ph = 0;
      uint32_t pq[32];
      {
        float acc[64];
        mainloop<128, 4, 5, 0, 16, false>(acc, ph, sb, w, t, ls);
        uint32_t qp[32];
#pragma unroll
        for (int i = 0; i < 32; i++) qp[i] = pack_bf16(acc[2 * i], acc[2 * i + 1]);
        mbar_wait(sb + B_WPHI, 1);
        const uint64_t dW = make_desc(sb + SM_X, 16, 512, 2);
        float p[4][16];
        wg_fence();
#pragma unroll
        for (int h = 0; h < 4; h++) wgmma_rs_n32(p[h], qp[8 * h], qp[8 * h + 1], qp[8 * h + 2], qp[8 * h + 3], dW + h * 128, 0);
#pragma unroll
        for (int h = 0; h < 4; h++) wgmma_rs_n32(p[h], qp[8 * h + 4], qp[8 * h + 5], qp[8 * h + 6], qp[8 * h + 7], dW + h * 128 + 64, 1);
        wg_commit();
        wg_wait<0>();
#pragma unroll
        for (int h = 0; h < 4; h++) {
          fence_regs(p[h]);
#pragma unroll
          for (int i = 0; i < 8; i++) pq[8 * h + i] = pack_bf16(p[h][2 * i], p[h][2 * i + 1]);
        }
      }
      float acc[64];
      mainloop<128, 4, 5, 1, 8, false, false, true>(acc, ph, sb, w, t, ls);
      mbar_wait(sb + B_SFREE, 0);
#pragma unroll
      for (int h = 0; h < 4; h++) {
        const uint32_t tb = sb + SM_STGH + (h >> 1) * 16384 + st_row;
        stsm_x4(tb + ((((h & 1) * 4 + 0 + st_hi) ^ st_x) << 4), pq[8 * h], pq[8 * h + 1], pq[8 * h + 2], pq[8 * h + 3]);
        stsm_x4(tb + ((((h & 1) * 4 + 2 + st_hi) ^ st_x) << 4), pq[8 * h + 4], pq[8 * h + 5], pq[8 * h + 6], pq[8 * h + 7]);
      }
      mbar_arrive(sb + B_DUMP + 24);
      mainloop<128, 4, 5, 4, 48, true, true, true, 3>(acc, ph, sb, w, t, ls);
      float acc2[64];
      mbar_wait(sb + B_GATES, 0);
      const float s0 = 1.f - lds_f32(sb + SM_GATE + 4 * rloc), s1 = 1.f - lds_f32(sb + SM_GATE + 4 * (rloc + 8));
#pragma unroll
      for (int j = 0; j < 16; j++) {
        const uint32_t bb = __float_as_uint(lds_f32(sb + SM_B2 + 2 * (8 * j + 2 * q)));
        acc2[4 * j] = s0 * bf_lo(bb); acc2[4 * j + 1] = s0 * bf_hi(bb);
        acc2[4 * j + 2] = s1 * bf_lo(bb); acc2[4 * j + 3] = s1 * bf_hi(bb);
      }
      mainloop<128, 4, 5, 2, 16, true, true, false, 1>(acc2, ph, sb, w, t, ls);
      fence_regs(acc);
      const float h0 = 0.5f * s0, h1 = 0.5f * s1;
      const uint32_t stg = sb + SM_RING + w * 8192 + (st_row - w * 8192);
#pragma unroll
      for (int half = 0; half < 2; half++) {
#pragma unroll
        for (int i = 4 * half; i < 4 * half + 4; i++) {
          const float* a1 = acc + 8 * i;
          const float* a2 = acc2 + 8 * i;
          const uint32_t r0 = pack_bf16(fmaf(a1[0], h0, a2[0]), fmaf(a1[1], h0, a2[1]));
          const uint32_t r1 = pack_bf16(fmaf(a1[2], h1, a2[2]), fmaf(a1[3], h1, a2[3]));
          const uint32_t r2 = pack_bf16(fmaf(a1[4], h0, a2[4]), fmaf(a1[5], h0, a2[5]));
          const uint32_t r3 = pack_bf16(fmaf(a1[6], h1, a2[6]), fmaf(a1[7], h1, a2[7]));
          stsm_x4(stg + half * 32768 + (((2 * (i & 3) + st_hi) ^ st_x) << 4), r0, r1, r2, r3);
        }
        fence_async_smem();
        if (w == 0) asm volatile("bar.sync 2, 128;" ::: "memory");
        else asm volatile("bar.sync 3, 128;" ::: "memory");
        if (t == 0) {
          tma_store_2d(&P.out, sb + SM_RING + w * 8192 + half * 32768, 128 * nn + 64 * half, m * 128 + w * 64);
          asm volatile("cp.async.bulk.commit_group;" ::: "memory");
        }
      }
      if (t == 0) asm volatile("cp.async.bulk.wait_group.read 0;" ::: "memory");
    }
  } else {
    asm volatile("setmaxnreg.inc.sync.aligned.u32 136;");
    CTA_CONTEXT();
    const int warp = t >> 5, lane = t & 31, q = lane & 3;
    uint32_t ep = 0;
    if (t == 0) {
      mbar_expect_tx(sb + B_WPHI, 8192);
      tma_2d(sb + SM_X, &P.wphi, sb + B_WPHI, 0, nn * 128);
      ep = load_epoch();
    }
    {
      const int r0 = m * 128 + nn * 16 + warp * 4;
      uint4 gw[4], xb[4][4];
#pragma unroll
      for (int u = 0; u < 4; u++)
#pragma unroll
        for (int i = 0; i < 4; i++)
          xb[u][i] = __ldg(reinterpret_cast<const uint4*>(P.A_x + (size_t)(r0 + u) * D_) + lane + 32 * i);
#pragma unroll
      for (int i = 0; i < 4; i++) gw[i] = __ldg(reinterpret_cast<const uint4*>(P.gate_w) + lane + 32 * i);
      {
        uint4* z = reinterpret_cast<uint4*>(g_kv + (size_t)nn * 4 * 64 * KVP) + m * 160;
        z[t] = make_uint4(0, 0, 0, 0);
        if (t < 32) z[128 + t] = make_uint4(0, 0, 0, 0);
      }
#pragma unroll
      for (int u = 0; u < 4; u++) {
        float sum = 0.f, dot = 0.f;
#pragma unroll
        for (int i = 0; i < 4; i++) {
          const uint32_t b[4] = {xb[u][i].x, xb[u][i].y, xb[u][i].z, xb[u][i].w};
          const uint32_t g[4] = {gw[i].x, gw[i].y, gw[i].z, gw[i].w};
#pragma unroll
          for (int k = 0; k < 4; k++) {
            sum += bf_lo(b[k]) + bf_hi(b[k]);
            dot = fmaf(bf_lo(b[k]), bf_lo(g[k]), dot);
            dot = fmaf(bf_hi(b[k]), bf_hi(g[k]), dot);
          }
        }
        const float mean = warp_sum(sum) * (1.f / D_);
        dot = warp_sum(dot);
        float var = 0.f;
#pragma unroll
        for (int i = 0; i < 4; i++) {
          const uint32_t b[4] = {xb[u][i].x, xb[u][i].y, xb[u][i].z, xb[u][i].w};
#pragma unroll
          for (int k = 0; k < 4; k++) {
            const float d0 = bf_lo(b[k]) - mean, d1 = bf_hi(b[k]) - mean;
            var = fmaf(d0, d0, var);
            var = fmaf(d1, d1, var);
          }
        }
        var = warp_sum(var) * (1.f / D_);
        const float rstd = rsqrtf(var + 1e-5f);
        uint4* dsty = reinterpret_cast<uint4*>(P.py + (size_t)(r0 + u) * PY) + lane;
#pragma unroll
        for (int i = 0; i < 4; i++) {
          const uint32_t b[4] = {xb[u][i].x, xb[u][i].y, xb[u][i].z, xb[u][i].w};
          uint32_t o[4];
#pragma unroll
          for (int k = 0; k < 4; k++) o[k] = pack_bf16((bf_lo(b[k]) - mean) * rstd, (bf_hi(b[k]) - mean) * rstd);
          dsty[32 * i] = make_uint4(o[0], o[1], o[2], o[3]);
        }
        if (lane == 0) g_gate[r0 + u] = 1.f / (1.f + __expf(-dot));
      }
      fence_async_all();
      epi_bar();
      if (t == 0) {
        signal_flag(g_cnt + (C_Y + m) * 32);
        signal_flag(g_cnt + (C_ZERO + nn) * 32);
      }
    }
    asm volatile("barrier.cluster.wait.acquire.aligned;" ::: "memory");
    {
      for (int p = t; p < 224; p += 128) sts_f32(sb + SM_B1 + 4 * p, __uint_as_float(reinterpret_cast<const uint32_t*>(P.b1)[224 * nn + p]));
      if (t < 64) sts_f32(sb + SM_B2 + 4 * t, __uint_as_float(reinterpret_cast<const uint32_t*>(P.b2)[64 * nn + t]));
      if (t == 0) {
        wait_flag(g_cnt + (C_Y + m) * 32, ep * 8);
        wait_flag(g_cnt + (C_ZERO + nn) * 32, ep * 16);
      }
      epi_bar();
      sts_f32(sb + SM_GATE + 4 * t, __ldcg(g_gate + m * 128 + t));
      mbar_arrive(sb + B_GATES);
      epi_bar();
    }
    const uint32_t my_row = t * 128, my_x = t & 7;
    {
      mbar_wait_sleep(sb + B_DUMP + 0, 0);
      const uint64_t dPhi = make_desc(sb + SM_X, 1024, 1024, 1);
      float kv[20];
#pragma unroll
      for (int i = 0; i < 20; i++) kv[i] = 0.f;
      float* dst = g_kv + ((size_t)(nn * 4) * 64 + warp * 16 + (lane >> 2)) * KVP;
#pragma unroll 1
      for (int h = 0; h < 4; h++) {
        const uint32_t tb = sb + SM_STG + h * 16384 + my_row;
        uint32_t pw[16];
#pragma unroll
        for (int c = 0; c < 4; c++) {
          const uint4 v = lds128(tb + (((4 + c) ^ my_x) << 4));
          pw[4 * c] = v.x; pw[4 * c + 1] = v.y; pw[4 * c + 2] = v.z; pw[4 * c + 3] = v.w;
        }
        sts128(tb + ((4 ^ my_x) << 4), 0x00003f80u, 0u, 0u, 0u);
        uint32_t phi[32];
        hedgehog_row<false>(pw, phi, 0);
        if (h > 0) {
          wg_wait<0>();
          fence_regs(kv);
#pragma unroll
          for (int j = 0; j < 4; j++) {
            asm volatile("red.global.add.v2.f32 [%0], {%1, %2};" ::"l"(dst + 8 * j + 2 * q), "f"(kv[4 * j]), "f"(kv[4 * j + 1]) : "memory");
            asm volatile("red.global.add.v2.f32 [%0], {%1, %2};" ::"l"(dst + 8 * KVP + 8 * j + 2 * q), "f"(kv[4 * j + 2]), "f"(kv[4 * j + 3]) : "memory");
          }
          if (q == 0) {
            asm volatile("red.global.add.f32 [%0], %1;" ::"l"(dst + 32), "f"(kv[16]) : "memory");
            asm volatile("red.global.add.f32 [%0], %1;" ::"l"(dst + 8 * KVP + 32), "f"(kv[18]) : "memory");
          }
          dst += 64 * KVP;
        }
        epi_bar();
#pragma unroll
        for (int c = 0; c < 8; c++)
          sts128(sb + SM_X + my_row + ((c ^ my_x) << 4), phi[4 * c], phi[4 * c + 1], phi[4 * c + 2], phi[4 * c + 3]);
        fence_async_smem();
        epi_bar();
        const uint64_t dV = make_desc(sb + SM_STG + h * 16384, 1024, 1024, 1);
        wg_fence();
#pragma unroll
        for (int k = 0; k < 8; k++) wgmma_ss_n40_tt(kv, dPhi + k * 128, dV + k * 128, k);
        wg_commit();
      }
      wg_wait<0>();
      fence_regs(kv);
      mbar_arrive(sb + B_SFREE);
#pragma unroll
      for (int j = 0; j < 4; j++) {
        asm volatile("red.global.add.v2.f32 [%0], {%1, %2};" ::"l"(dst + 8 * j + 2 * q), "f"(kv[4 * j]), "f"(kv[4 * j + 1]) : "memory");
        asm volatile("red.global.add.v2.f32 [%0], {%1, %2};" ::"l"(dst + 8 * KVP + 8 * j + 2 * q), "f"(kv[4 * j + 2]), "f"(kv[4 * j + 3]) : "memory");
      }
      if (q == 0) {
        asm volatile("red.global.add.f32 [%0], %1;" ::"l"(dst + 32), "f"(kv[16]) : "memory");
        asm volatile("red.global.add.f32 [%0], %1;" ::"l"(dst + 8 * KVP + 32), "f"(kv[18]) : "memory");
      }
      epi_bar();
      if (t == 0) {
        mbar_expect_tx(sb + B_WPHI, 8192);
        tma_2d(sb + SM_X, &P.wphi, sb + B_WPHI, 0, nn * 128);
        signal_flag(g_cnt + (C_KV + nn) * 32);
      }
    }
    {
      const uint4 b = lds128(sb + SM_B1 + 16 * lane);
      __nv_bfloat16* base = P.ph + (size_t)(m * 128 + warp * 32) * PH + 448 * nn + 8 * lane;
      const uint32_t src = sb + SM_STG + (lane >> 3) * 16384 + warp * 32 * 128;
      mbar_wait_sleep(sb + B_DUMP + 8, 0);
#pragma unroll 1
      for (int r = 0; r < 32; r += 2) {
        uint4 x[2];
#pragma unroll
        for (int u = 0; u < 2; u++) x[u] = lds128(src + (r + u) * 128 + (((lane & 7) ^ ((r + u) & 7)) << 4));
#pragma unroll
        for (int u = 0; u < 2; u++) *reinterpret_cast<uint4*>(base + (size_t)(r + u) * PH) = gelu8(x[u], b);
      }
      mbar_arrive(sb + B_SFREE);
      fence_async_all();
      epi_bar();
      if (t < 2) mbar_arrive_cluster(sb + B_SLO, t);
      if (t == 0) signal_flag(g_cnt + (C_H1 + m) * 32);
    }
    {
      uint4 b[3];
      int ro[3], co[3];
#pragma unroll
      for (int u = 0; u < 3; u++) {
        const int L = u * 32 + lane;
        ro[u] = L / 24;
        co[u] = L % 24;
        b[u] = lds128(sb + SM_B1 + 512 + 16 * co[u]);
      }
      __nv_bfloat16* base = P.ph + (size_t)(m * 128 + warp * 32) * PH + 448 * nn + 256;
      mbar_wait_sleep(sb + B_DUMP + 16, 0);
#pragma unroll 1
      for (int r = 0; r < 32; r += 4) {
        uint4 x[3];
#pragma unroll
        for (int u = 0; u < 3; u++) {
          const int row = warp * 32 + r + ro[u];
          x[u] = lds128(sb + SM_STGH + (co[u] >> 3) * 16384 + row * 128 + (((co[u] & 7) ^ (row & 7)) << 4));
        }
#pragma unroll
        for (int u = 0; u < 3; u++) *reinterpret_cast<uint4*>(base + (size_t)(r + ro[u]) * PH + 8 * co[u]) = gelu8(x[u], b[u]);
      }
      mbar_arrive(sb + B_SFREE);
      fence_async_all();
      epi_bar();
      if (t == 0) signal_flag(g_cnt + (C_H2 + m) * 32);
    }
    {
      constexpr uint32_t SM_Z = SM_B1, SM_DEN = SM_B1 + 1024;
      if (t == 0) wait_flag(g_cnt + (C_KV + nn) * 32, ep * 16);
      epi_bar();
      {
        const float* ksrc = g_kv + (size_t)(nn * 4) * 64 * KVP;
        const float z0 = __ldcg(ksrc + t * KVP + 32), z1 = __ldcg(ksrc + (128 + t) * KVP + 32);
#pragma unroll
        for (int hp = 0; hp < 2; hp++) {
          float4 kvv[8];
#pragma unroll
          for (int u = 0; u < 8; u++) {
            const int idx = (hp * 8 + u) * 128 + t;
            kvv[u] = __ldcg(reinterpret_cast<const float4*>(ksrc + (idx >> 3) * KVP + 4 * (idx & 7)));
          }
#pragma unroll
          for (int u = 0; u < 8; u++) {
            const int idx = (hp * 8 + u) * 128 + t, f = idx >> 3, c4 = idx & 7;
            asm volatile("st.shared.v2.u32 [%0], {%1, %2};" ::"r"(sb + SM_KVZ + f * 64 + (((c4 >> 1) ^ ((f >> 1) & 3)) << 4) + (c4 & 1) * 8),
                         "r"(pack_bf16(kvv[u].x, kvv[u].y)), "r"(pack_bf16(kvv[u].z, kvv[u].w)) : "memory");
          }
        }
        sts_f32(sb + SM_Z + 4 * t, bf_lo(pack_bf16(z0, z0)));
        sts_f32(sb + SM_Z + 4 * (128 + t), bf_lo(pack_bf16(z1, z1)));
      }
      mbar_wait_sleep(sb + B_DUMP + 24, 0);
      epi_bar();
#pragma unroll 1
      for (int h = 0; h < 4; h++) {
        const uint32_t tb = sb + SM_STGH + (h >> 1) * 16384 + my_row;
        uint32_t pw[16];
#pragma unroll
        for (int c = 0; c < 4; c++) {
          const uint4 v = lds128(tb + ((((h & 1) * 4 + c) ^ my_x) << 4));
          pw[4 * c] = v.x; pw[4 * c + 1] = v.y; pw[4 * c + 2] = v.z; pw[4 * c + 3] = v.w;
        }
        uint32_t phi[32];
        const float den = hedgehog_row<true>(pw, phi, sb + SM_Z + h * 256);
        epi_bar();
#pragma unroll
        for (int c = 0; c < 8; c++)
          sts128(sb + SM_X + my_row + ((c ^ my_x) << 4), phi[4 * c], phi[4 * c + 1], phi[4 * c + 2], phi[4 * c + 3]);
        sts_f32(sb + SM_DEN + 4 * t, lds_f32(sb + SM_GATE + 4 * t) * rcpf(den + 1e-6f));
        fence_async_smem();
        epi_bar();
        const uint64_t dK = make_desc(sb + SM_KVZ + h * 4096, 16, 512, 2);
        const uint64_t dQ = make_desc(sb + SM_X, 16, 1024, 1);
        float nd[2][16];
        wg_fence();
#pragma unroll
        for (int k = 0; k < 4; k++)
#pragma unroll
          for (int hf = 0; hf < 2; hf++) wgmma_ss_n32_nt(nd[hf], dQ + hf * 512 + k * 2, dK + k * 64, k);
        wg_commit();
        wg_wait<0>();
#pragma unroll
        for (int hf = 0; hf < 2; hf++) {
          fence_regs(nd[hf]);
          const int rl = hf * 64 + warp * 16 + (lane >> 2);
          const float f0 = lds_f32(sb + SM_DEN + 4 * rl), f1 = lds_f32(sb + SM_DEN + 4 * (rl + 8));
          const int srow = hf * 64 + warp * 16 + ((lane >> 3) & 1) * 8 + (lane & 7);
          const uint32_t ob = sb + SM_STGH + (h >> 1) * 16384 + srow * 128;
#pragma unroll
          for (int c = 0; c < 2; c++)
            stsm_x4(ob + ((((h & 1) * 4 + 2 * c + (lane >> 4)) ^ (srow & 7)) << 4),
                    pack_bf16(nd[hf][8 * c] * f0, nd[hf][8 * c + 1] * f0), pack_bf16(nd[hf][8 * c + 2] * f1, nd[hf][8 * c + 3] * f1),
                    pack_bf16(nd[hf][8 * c + 4] * f0, nd[hf][8 * c + 5] * f0), pack_bf16(nd[hf][8 * c + 6] * f1, nd[hf][8 * c + 7] * f1));
        }
      }
      fence_async_smem();
      epi_bar();
      if (t == 0) {
#pragma unroll
        for (int i = 0; i < 4; i++)
          tma_store_2d(&P.o, sb + SM_STGH + (i >> 1) * 16384 + (i & 1) * 8192, 128 * nn + (i >> 1) * 64, m * 128 + (i & 1) * 64);
        asm volatile("cp.async.bulk.commit_group;" ::: "memory");
        asm volatile("cp.async.bulk.wait_group 0;" ::: "memory");
        signal_flag(g_cnt + (C_O + m) * 32);
        asm volatile("red.relaxed.gpu.global.add.u32 [%0], 1;" ::"l"(g_cnt + C_DONE * 32) : "memory");
      }
    }
  }
}

typedef CUresult (*EncFn)(CUtensorMap*, CUtensorMapDataType, cuuint32_t, void*, const cuuint64_t*, const cuuint64_t*,
                          const cuuint32_t*, const cuuint32_t*, CUtensorMapInterleave, CUtensorMapSwizzle,
                          CUtensorMapL2promotion, CUtensorMapFloatOOBfill);

void encode(EncFn enc, CUtensorMap* m, int rank, const void* p, const cuuint64_t* dims, const cuuint64_t* strides,
            const cuuint32_t* box, CUtensorMapSwizzle swz, CUtensorMapL2promotion promo = CU_TENSOR_MAP_L2_PROMOTION_L2_256B) {
  cuuint32_t e[5] = {1, 1, 1, 1, 1};
  enc(m, CU_TENSOR_MAP_DATA_TYPE_BFLOAT16, rank, const_cast<void*>(p), dims, strides, box, e, CU_TENSOR_MAP_INTERLEAVE_NONE, swz,
      promo, CU_TENSOR_MAP_FLOAT_OOB_FILL_NONE);
}
void map_rows(EncFn enc, CUtensorMap* m, const void* p, int rows, int cols, int pitch, int boxrows = 64) {
  cuuint64_t d[2] = {(cuuint64_t)cols, (cuuint64_t)rows}, s[1] = {(cuuint64_t)pitch * 2};
  cuuint32_t b[2] = {64, (cuuint32_t)boxrows};
  encode(enc, m, 2, p, d, s, b, CU_TENSOR_MAP_SWIZZLE_128B, CU_TENSOR_MAP_L2_PROMOTION_L2_256B);
}
void map_w(EncFn enc, CUtensorMap* m, const void* p, int K, int N, int groups, int boxk = 64) {
  cuuint64_t d[3] = {64, (cuuint64_t)K, (cuuint64_t)N / 64}, s[2] = {(cuuint64_t)N * 2, 128};
  cuuint32_t b[3] = {64, (cuuint32_t)boxk, (cuuint32_t)groups};
  encode(enc, m, 3, p, d, s, b, CU_TENSOR_MAP_SWIZZLE_128B);
}
}

extern "C" void kernel_launch(void* const* d_in, const int* in_sizes, int n_in, void* d_out, int out_size) {
  (void)in_sizes; (void)n_in; (void)out_size;
  static EncFn enc = nullptr;
  static void *p_y, *p_h, *p_o;
  if (!enc) {
    void* fn = nullptr;
    cudaDriverEntryPointQueryResult qr;
    cudaGetDriverEntryPoint("cuTensorMapEncodeTiled", &fn, cudaEnableDefault, &qr);
    enc = (EncFn)fn;
    cudaGetSymbolAddress(&p_y, g_y);
    cudaGetSymbolAddress(&p_h, g_h);
    cudaGetSymbolAddress(&p_o, g_o);
    cudaFuncSetAttribute(fused_kernel, cudaFuncAttributeMaxDynamicSharedMemorySize, SM_TOTAL);
  }
  Params P;
  P.py = (__nv_bfloat16*)p_y; P.ph = (__nv_bfloat16*)p_h; P.po = (__nv_bfloat16*)p_o;
  map_rows(enc, &P.xa, d_in[0], S_, D_, D_);
  map_rows(enc, &P.y, p_y, S_, D_, PY);
  map_rows(enc, &P.h, p_h, S_, F_, PH);
  map_rows(enc, &P.o, p_o, S_, D_, PO);
  map_rows(enc, &P.out, d_out, S_, D_, D_);
  map_w(enc, &P.wqkv, d_in[1], D_, 3 * D_, 2);
  map_w(enc, &P.wqkv32, d_in[1], D_, 3 * D_, 2, 32);
  map_w(enc, &P.w1a, d_in[5], D_, F_, 4, 32);
  map_w(enc, &P.w1b, d_in[5], D_, F_, 3, 32);
  map_w(enc, &P.w2, d_in[7], F_, D_, 2);
  map_w(enc, &P.wo, d_in[3], D_, D_, 2);
  {
    cuuint64_t d[2] = {32, 1024}, s[1] = {64};
    cuuint32_t b[2] = {32, 128};
    encode(enc, &P.wphi, 2, d_in[2], d, s, b, CU_TENSOR_MAP_SWIZZLE_64B);
  }
  P.A_x = (const __nv_bfloat16*)d_in[0];
  P.b1 = (const __nv_bfloat16*)d_in[6];
  P.b2 = (const __nv_bfloat16*)d_in[8];
  P.gate_w = (const __nv_bfloat16*)d_in[9];
  fused_kernel<<<NCTA, 512, SM_TOTAL, cudaStreamPerThread>>>(P);
}
```
